```python
import torch

def _softmax(x, axis=-1):
    return torch.softmax(x, dim=axis)
def _gelu(x):
    return torch.nn.functional.gelu(x, approximate="tanh")
def _silu(x):
    return torch.nn.functional.silu(x)
def _sigmoid(x):
    return torch.sigmoid(x)
def _layernorm(x, axis=-1, eps=1e-5):
    m = x.mean(dim=axis, keepdim=True)
    v = x.var(dim=axis, keepdim=True, unbiased=False)
    return (x - m) / torch.sqrt(v + eps)
def _scatter_add(tgt, idx, src, axis=0):
    return tgt.clone().index_add_(axis, idx, src)
def _segment_sum(src, seg, n):
    out = torch.zeros((n,) + src.shape[1:], dtype=src.dtype)
    return out.index_add_(0, seg, src)
def _pad(x, pw):
    flat = tuple(v for pair in reversed(pw) for v in pair)
    return torch.nn.functional.pad(x, flat)

kernel_name = 'recurrent_scan__linear_kernel_hedgehog__dense_activation_silu__prompt'

def setup_inputs():

    _w = (lambda a: (lambda t: t.to(torch.bfloat16) if t.is_floating_point() else t)(torch.as_tensor(a)))
    def _A_setup():
        B, S, D, H = 1, 2048, 640, 32
        Dh = D // H
        return {
            "x": _w((lambda *s: torch.randn(*s, dtype=torch.bfloat16) * 0.05)(B, S, D)),
            "wqkv": _w((lambda *s: torch.randn(*s, dtype=torch.bfloat16) * 0.4)(D, 3 * D)),
            "w_phi": _w((lambda *s: torch.randn(*s, dtype=torch.bfloat16) * 0.4)(H, Dh, Dh) * (Dh ** -0.5)),
            "wo": _w((lambda *s: torch.randn(*s, dtype=torch.bfloat16) * 0.2)(D, D)),
        }
    _A_in = _A_setup()

    def _B_setup():
        B, S, D, F = 1, 2048, 640, 1536
        return {
            "x": _w((lambda *s: torch.randn(*s, dtype=torch.bfloat16) * 0.05)(B, S, D)),
            "w1": _w((lambda *s: torch.randn(*s, dtype=torch.bfloat16) * 0.4)(D, F) * (D ** -0.5)),
            "w2": _w((lambda *s: torch.randn(*s, dtype=torch.bfloat16) * 0.1)(F, D) * (F ** -0.5)),
        }
    _B_in = _B_setup()

    return {
        "A_x": _A_in["x"],
        "A_wqkv": _A_in["wqkv"],
        "A_w_phi": _A_in["w_phi"],
        "A_wo": _A_in["wo"],
        "B_x": _B_in["x"],
        "B_w1": _B_in["w1"],
        "B_w2": _B_in["w2"],
    }

def reference(A_x, A_wqkv, A_w_phi, A_wo, B_x, B_w1, B_w2):
    def _A_ref(x, wqkv, w_phi, wo):
        B, S, D = x.shape
        H = 32; Dh = D // H
        qkv = (lambda x, *d: x.permute(*d))((x @ wqkv).reshape(B, S, 3, H, Dh), 2, 0, 3, 1, 4)
        q, k, v = qkv[0], qkv[1], qkv[2]
        pq = torch.einsum("bhsd,hdf->bhsf", q, w_phi)
        pk = torch.einsum("bhsd,hdf->bhsf", k, w_phi)
        phi_q = torch.concatenate([_softmax(pq, axis=-1), _softmax(-pq, axis=-1)], axis=-1)
        phi_k = torch.concatenate([_softmax(pk, axis=-1), _softmax(-pk, axis=-1)], axis=-1)
        kv = torch.einsum("bhsf,bhsd->bhfd", phi_k, v)
        z  = torch.einsum("bhsf->bhf", phi_k)
        num = torch.einsum("bhqf,bhfd->bhqd", phi_q, kv)
        den = torch.einsum("bhqf,bhf->bhq", phi_q, z)[..., None] + 1e-6
        o = num / den
        return (lambda x, *d: x.permute(*d))(o, 0, 2, 1, 3).reshape(B, S, D) @ wo

    def _B_ref(x, w1, w2):
        h = torch.einsum("bsd,df->bsf", x, w1)
        h = _silu(h)
        out = torch.einsum("bsf,fd->bsd", h, w2)
        return out

    x = A_x
    xn = _layernorm(x, axis=-1)
    s = _A_ref(xn, A_wqkv, A_w_phi, A_wo)
    g = _silu(_B_ref(xn, B_w1, B_w2))
    return x + s * g
```

```cpp
#include <cuda_runtime.h>
#include <cuda_bf16.h>
#include <cuda.h>
#include <stdint.h>
#include <type_traits>

namespace hh {

constexpr int SEQ = 2048, DM = 640, FF = 1536;
constexpr int NCTA = 128;
constexpr int NGRID = 132;
constexpr int NSLOT = 5;
constexpr int SLOT_BYTES = 36864;
constexpr int OFF_STG = NSLOT * SLOT_BYTES;
constexpr int STG_BYTES = 40960;
constexpr int OFF_CS = OFF_STG + STG_BYTES;
constexpr int OFF_ROWC = OFF_CS + 1728;
constexpr int OFF_BAR = OFF_ROWC + 1024;
constexpr int OFF_PHI = OFF_BAR + 384;
constexpr int OFF_T0 = OFF_PHI + 3200;
constexpr int SMEM_USED_BASE = OFF_T0 + 16;
constexpr int SMEM_USED = SMEM_USED_BASE;
constexpr int SMEM_ALLOC = SMEM_USED;
constexpr int B_FULL = 0, B_EMPTY = 40, B_CONST = 80, B_XF = 104, B_PIN = 112, B_SDONE = 120, B_PINQ = 88;
constexpr int B_GO2 = 128, B_GO3 = 136, B_GO4 = 144, B_GO5 = 152, B_GO6 = 160, B_KVP = 168, B_KVS = 176, B_QS = 184, B_CONSTQ = 192, B_GATE3 = 200, B_GATE4 = 208, B_HAP = 216, B_HBP = 224, B_KVOK = 232, B_KVP0 = 240, B_KVF = 248, B_E2E = 96;
constexpr int NSLOT2 = 6, SLOT2_BYTES = 28672, B_FULL2 = 256, B_EMPTY2 = 304;
constexpr int WIN_OFF = 0, WOUT_KV = 19200, WOUT_Q = 32000;
constexpr int PHI_HS = 5152, V_OFF = 4 * PHI_HS, V_HS = 3104;
constexpr int BKV_LBO = 1408, OST_OFF = 28160;
constexpr int XO_OFF = 20480;
enum { FL_STATS = 0, FL_PREP = 16, FL_P3W = 24, FL_HA = 32, FL_HB = 48, FL_KV = 64, FL_O = 72, FL_CS = 88, FL_W1T = 96, FL_E2D = 104, FL_E1D = 120, FL_N = 136 };
enum { NB_A = 1, NB_B = 2, NB_A2B = 3, NB_B2A = 4, NB_STG = 5, NB_G = 6, NB_AUX = 7 };

#define T3_GO -1
#define T0_DELAY 900
#define T4_LEAD 256
#define T4_PACE 180
#define PACE2 320
#define PACE3 288
#define PACE4 160
constexpr float LOG2E = 1.4426950408889634f;
constexpr uint32_t SBASE = 1024;

__device__ __align__(1024) uint8_t g_wkv[8 * 10 * 20480];
__device__ __align__(1024) uint8_t g_wqh[8 * 80 * 2304];
__device__ __align__(1024) uint8_t g_wp3[8 * 34 * 10240];
__device__ __align__(1024) __nv_bfloat16 g_h[SEQ * FF];
__device__ __align__(1024) __nv_bfloat16 g_o[SEQ * DM];
__device__ __align__(128) float2 g_stats[SEQ];
__device__ __align__(128) float g_cs[2][8 * 432];
__device__ __align__(128) float g_kv[2][32 * 24 * 40];
__device__ __align__(128) unsigned g_flags[FL_N * 32];
__device__ __align__(128) unsigned g_epoch[32];
__device__ __align__(128) unsigned long long g_t0[8 * 16];
#define TL(slot) do {} while (0)
#define TLG(slot) do {} while (0)
#define PTL(slot) do {} while (0)

struct Params {
  CUtensorMap tm_x;
  CUtensorMap tm_h;
  CUtensorMap tm_o;
  CUtensorMap tm_xt;
  CUtensorMap tm_ost;
  CUtensorMap tm_out;
  CUtensorMap tm_wqkv;
  CUtensorMap tm_w2;
  CUtensorMap tm_wo;
  CUtensorMap tm_w1b;
  const __nv_bfloat16* x;
  const __nv_bfloat16* wqkv;
  const __nv_bfloat16* wphi;
  const __nv_bfloat16* wo;
  const __nv_bfloat16* w1;
  const __nv_bfloat16* w2;
};

__device__ __forceinline__ uint32_t smem_u32(const void* p) { return (uint32_t)__cvta_generic_to_shared(p); }
__device__ __forceinline__ void mbar_init(uint32_t bar, uint32_t cnt) { asm volatile("mbarrier.init.shared::cta.b64 [%0], %1;" ::"r"(bar), "r"(cnt) : "memory"); }
__device__ __forceinline__ void mbar_expect_tx(uint32_t bar, uint32_t bytes) { asm volatile("mbarrier.arrive.expect_tx.shared::cta.b64 _, [%0], %1;" ::"r"(bar), "r"(bytes) : "memory"); }
__device__ __forceinline__ void mbar_arrive(uint32_t bar) { asm volatile("mbarrier.arrive.shared::cta.b64 _, [%0];" ::"r"(bar) : "memory"); }
__device__ __forceinline__ void mbar_wait(uint32_t bar, uint32_t parity) {
  uint32_t ok;
  int it = 0;
  do {
    asm volatile("{\n.reg .pred p;\nmbarrier.try_wait.parity.shared::cta.b64 p, [%1], %2;\nselp.u32 %0, 1, 0, p;\n}" : "=r"(ok) : "r"(bar), "r"(parity) : "memory");
  } while (!ok && ++it < (1 << 17));
}
__device__ __forceinline__ void mbar_wait_trap(uint32_t bar, uint32_t parity) {
  uint32_t ok;
  int it = 0;
  do {
    asm volatile("{\n.reg .pred p;\nmbarrier.try_wait.parity.shared::cta.b64 p, [%1], %2;\nselp.u32 %0, 1, 0, p;\n}" : "=r"(ok) : "r"(bar), "r"(parity) : "memory");
    if (!ok && ++it > (1 << 20)) __trap();
  } while (!ok);
}
__device__ __forceinline__ void tma2d(uint32_t dst, const CUtensorMap* tm, int c0, int c1, uint32_t bar) {
  asm volatile("cp.async.bulk.tensor.2d.shared::cluster.global.mbarrier::complete_tx::bytes [%0], [%1, {%3, %4}], [%2];" ::"r"(dst), "l"(tm), "r"(bar), "r"(c0), "r"(c1) : "memory");
}
__device__ __forceinline__ void tma3d(uint32_t dst, const CUtensorMap* tm, int c0, int c1, int c2, uint32_t bar) {
  asm volatile("cp.async.bulk.tensor.3d.shared::cluster.global.mbarrier::complete_tx::bytes [%0], [%1, {%3, %4, %5}], [%2];" ::"r"(dst), "l"(tm), "r"(bar), "r"(c0), "r"(c1), "r"(c2) : "memory");
}
__device__ __forceinline__ void bulk1d_store(void* dst, uint32_t src, uint32_t bytes) {
  asm volatile("cp.async.bulk.global.shared::cta.bulk_group [%0], [%1], %2;" ::"l"(dst), "r"(src), "r"(bytes) : "memory");
}
__device__ __forceinline__ void tma2d_store(const CUtensorMap* tm, int c0, int c1, uint32_t src) {
  asm volatile("cp.async.bulk.tensor.2d.global.shared::cta.bulk_group [%0, {%2, %3}], [%1];" ::"l"(tm), "r"(src), "r"(c0), "r"(c1) : "memory");
}
__device__ __forceinline__ void bulk1d(uint32_t dst, const void* src, uint32_t bytes, uint32_t bar) {
  asm volatile("cp.async.bulk.shared::cluster.global.mbarrier::complete_tx::bytes [%0], [%1], %2, [%3];" ::"r"(dst), "l"(src), "r"(bytes), "r"(bar) : "memory");
}
__device__ __forceinline__ void bulk_commit() { asm volatile("cp.async.bulk.commit_group;" ::: "memory"); }
__device__ __forceinline__ void bulk_wait_read0() { asm volatile("cp.async.bulk.wait_group.read 0;" ::: "memory"); }
__device__ __forceinline__ void bulk_wait0() { asm volatile("cp.async.bulk.wait_group 0;" ::: "memory"); }
__device__ __forceinline__ void fence_async_global() { asm volatile("fence.proxy.async.global;" ::: "memory"); }
__device__ __forceinline__ void fence_async_smem() { asm volatile("fence.proxy.async.shared::cta;" ::: "memory"); }
__device__ __forceinline__ void fence_gpu() { asm volatile("fence.acq_rel.gpu;" ::: "memory"); }
__device__ __forceinline__ void nb_sync(int id, int n) { asm volatile("bar.sync %0, %1;" ::"r"(id), "r"(n) : "memory"); }
__device__ __forceinline__ void nb_arrive(int id, int n) { asm volatile("bar.arrive %0, %1;" ::"r"(id), "r"(n) : "memory"); }
__device__ __forceinline__ void wg_fence() { asm volatile("wgmma.fence.sync.aligned;" ::: "memory"); }
__device__ __forceinline__ void wg_commit() { asm volatile("wgmma.commit_group.sync.aligned;" ::: "memory"); }
template <int N> __device__ __forceinline__ void wg_wait() { asm volatile("wgmma.wait_group.sync.aligned %0;" ::"n"(N) : "memory"); }
template <int N> __device__ __forceinline__ void reg_fence(float (&d)[N]) {
#pragma unroll
  for (int i = 0; i < N; i++) asm volatile("" : "+f"(d[i])::"memory");
}
#define FLAG_BACKOFF __nanosleep(20)
__device__ __forceinline__ void flag_add(int idx) { asm volatile("red.release.gpu.global.add.u32 [%0], 1;" ::"l"(&g_flags[idx * 32]) : "memory"); }
__device__ __forceinline__ void flag_add_relaxed(int idx) { asm volatile("red.relaxed.gpu.global.add.u32 [%0], 1;" ::"l"(&g_flags[idx * 32]) : "memory"); }
template <bool ALL>
__device__ __forceinline__ void flag_poll(const unsigned* p, unsigned target) {
  int it = 0;
  while (true) {
    unsigned v;
    asm volatile("ld.relaxed.gpu.global.u32 %0, [%1];" : "=r"(v) : "l"(p) : "memory");
    const bool ok = (int)(v - target) >= 0;
    if (ALL ? (bool)__all_sync(0xffffffffu, ok) : ok) break;
    if (++it > (1 << 21)) __trap();
    FLAG_BACKOFF;
  }
  asm volatile("fence.acquire.gpu;" ::: "memory");
}
__device__ __forceinline__ void flag_wait(int idx, unsigned target) { flag_poll<false>(&g_flags[idx * 32], target); }
__device__ __forceinline__ void flag_wait8(int idx, unsigned target, int lane) { flag_poll<true>(&g_flags[(idx + (lane & 7)) * 32], target); }
__device__ __forceinline__ void flag_wait2(int idx0, unsigned t0, int idx1, unsigned t1, int lane) {
  flag_poll<true>(&g_flags[((lane & 1) ? idx1 : idx0) * 32], (lane & 1) ? t1 : t0);
}
__device__ __forceinline__ uint32_t gtime() { uint32_t t; asm volatile("mov.u32 %0, %%globaltimer_lo;" : "=r"(t)); return t; }
__device__ __forceinline__ void wait_until(uint32_t t) { while ((int)(gtime() - t) < 0) {} }
__device__ __forceinline__ unsigned ld_epoch() {
  unsigned v;
  asm volatile("ld.relaxed.gpu.global.u32 %0, [%1];" : "=r"(v) : "l"(&g_epoch[0]) : "memory");
  return v;
}
template <uint32_t OFF, uint32_t LBO, uint32_t SBO, uint32_t SWZ>
__device__ __forceinline__ uint64_t mkdesc(uint32_t a16) {
  const uint32_t lo = a16 + ((OFF >> 4) | ((LBO >> 4) << 16));
  constexpr uint32_t hi = (SBO >> 4) | (SWZ << 30);
  return ((uint64_t)hi << 32) | lo;
}
template <uint32_t OFF, uint32_t LBO = 16> __device__ __forceinline__ uint64_t desc_sw128(uint32_t a16) { return mkdesc<OFF, LBO, 1024, 1>(a16); }
template <uint32_t OFF, uint32_t LBO, uint32_t SBO> __device__ __forceinline__ uint64_t desc_nosw(uint32_t a16) { return mkdesc<OFF, LBO, SBO, 0>(a16); }
template <int I, int N, class F> __device__ __forceinline__ void static_for(F&& f) {
  if constexpr (I < N) { f(std::integral_constant<int, I>{}); static_for<I + 1, N>(f); }
}
__device__ __forceinline__ float ex2(float x) { float y; asm("ex2.approx.ftz.f32 %0, %1;" : "=f"(y) : "f"(x)); return y; }
__device__ __forceinline__ float rcp(float x) { float y; asm("rcp.approx.ftz.f32 %0, %1;" : "=f"(y) : "f"(x)); return y; }
__device__ __forceinline__ float sqrt_fast(float x) { float y; asm("sqrt.approx.ftz.f32 %0, %1;" : "=f"(y) : "f"(x)); return y; }
__device__ __forceinline__ float tanh_fast(float x) { float y; asm("tanh.approx.f32 %0, %1;" : "=f"(y) : "f"(x)); return y; }
__device__ __forceinline__ float silu_half(float h) { return fmaf(h, tanh_fast(h), h); }
__device__ __forceinline__ uint32_t pack2(float lo, float hi) { uint32_t r; asm("cvt.rn.bf16x2.f32 %0, %1, %2;" : "=r"(r) : "f"(hi), "f"(lo)); return r; }
__device__ __forceinline__ float bf_lo(uint32_t v) { return __uint_as_float(v << 16); }
__device__ __forceinline__ float bf_hi(uint32_t v) { return __uint_as_float(v & 0xFFFF0000u); }
__device__ __forceinline__ float bf_round(float x) { return __bfloat162float(__float2bfloat16_rn(x)); }
__device__ __forceinline__ uint32_t ldg32(const void* p) { uint32_t v; asm volatile("ld.global.nc.u32 %0, [%1];" : "=r"(v) : "l"(p)); return v; }
__device__ __forceinline__ uint32_t ldg16(const void* p) { unsigned short v; asm volatile("ld.global.nc.u16 %0, [%1];" : "=h"(v) : "l"(p)); return v; }
__device__ __forceinline__ uint4 ldg128(const void* p) { uint4 v; asm volatile("ld.global.nc.v4.u32 {%0,%1,%2,%3}, [%4];" : "=r"(v.x), "=r"(v.y), "=r"(v.z), "=r"(v.w) : "l"(p)); return v; }
__device__ __forceinline__ float ldcg_f(const float* p) { float v; asm volatile("ld.relaxed.gpu.global.f32 %0, [%1];" : "=f"(v) : "l"(p) : "memory"); return v; }
__device__ __forceinline__ float2 ldcg_f2(const float2* p) { float2 v; asm volatile("ld.relaxed.gpu.global.v2.f32 {%0,%1}, [%2];" : "=f"(v.x), "=f"(v.y) : "l"(p) : "memory"); return v; }
__device__ __forceinline__ float4 ldcg_f4(const float* p) { float4 v; asm volatile("ld.relaxed.gpu.global.v4.f32 {%0,%1,%2,%3}, [%4];" : "=f"(v.x), "=f"(v.y), "=f"(v.z), "=f"(v.w) : "l"(p) : "memory"); return v; }
__device__ __forceinline__ uint32_t lds32(uint32_t a) { uint32_t v; asm volatile("ld.shared.u32 %0, [%1];" : "=r"(v) : "r"(a) : "memory"); return v; }
__device__ __forceinline__ uint32_t lds16(uint32_t a) { unsigned short v; asm volatile("ld.shared.u16 %0, [%1];" : "=h"(v) : "r"(a) : "memory"); return v; }
__device__ __forceinline__ void sts32(uint32_t a, uint32_t x) { asm volatile("st.shared.u32 [%0], %1;" ::"r"(a), "r"(x) : "memory"); }
__device__ __forceinline__ void sts128(uint32_t a, uint32_t x, uint32_t y, uint32_t z, uint32_t w) { asm volatile("st.shared.v4.u32 [%0], {%1,%2,%3,%4};" ::"r"(a), "r"(x), "r"(y), "r"(z), "r"(w) : "memory"); }
__device__ __forceinline__ void sts64(uint32_t a, uint32_t x, uint32_t y) { asm volatile("st.shared.v2.u32 [%0], {%1,%2};" ::"r"(a), "r"(x), "r"(y) : "memory"); }
__device__ __forceinline__ uint4 lds128(uint32_t a) { uint4 v; asm volatile("ld.shared.v4.u32 {%0,%1,%2,%3}, [%4];" : "=r"(v.x), "=r"(v.y), "=r"(v.z), "=r"(v.w) : "r"(a) : "memory"); return v; }
__device__ __forceinline__ uint2 lds64(uint32_t a) { uint2 v; asm volatile("ld.shared.v2.u32 {%0,%1}, [%2];" : "=r"(v.x), "=r"(v.y) : "r"(a) : "memory"); return v; }
__device__ __forceinline__ float2 lds_f2(uint32_t a) { float2 v; asm volatile("ld.shared.v2.f32 {%0,%1}, [%2];" : "=f"(v.x), "=f"(v.y) : "r"(a) : "memory"); return v; }
__device__ __forceinline__ void red_f32(float* p, float v) { asm volatile("red.relaxed.gpu.global.add.f32 [%0], %1;" ::"l"(p), "f"(v) : "memory"); }
__device__ __forceinline__ void red_f32x2(float* p, float a, float b) { asm volatile("red.relaxed.gpu.global.add.v2.f32 [%0], {%1, %2};" ::"l"(p), "f"(a), "f"(b) : "memory"); }
__device__ __forceinline__ void mma16816_z(float (&c)[4], uint32_t a0, uint32_t a1, uint32_t a2, uint32_t a3, uint32_t b0, uint32_t b1) {
  asm volatile("mma.sync.aligned.m16n8k16.row.col.f32.bf16.bf16.f32 {%0,%1,%2,%3}, {%4,%5,%6,%7}, {%8,%9}, {%10,%10,%10,%10};"
               : "=f"(c[0]), "=f"(c[1]), "=f"(c[2]), "=f"(c[3])
               : "r"(a0), "r"(a1), "r"(a2), "r"(a3), "r"(b0), "r"(b1), "f"(0.f));
}
__device__ __forceinline__ void mma16816(float (&c)[4], uint32_t a0, uint32_t a1, uint32_t a2, uint32_t a3, uint32_t b0, uint32_t b1) {
  asm volatile("mma.sync.aligned.m16n8k16.row.col.f32.bf16.bf16.f32 {%0,%1,%2,%3}, {%4,%5,%6,%7}, {%8,%9}, {%0,%1,%2,%3};"
               : "+f"(c[0]), "+f"(c[1]), "+f"(c[2]), "+f"(c[3])
               : "r"(a0), "r"(a1), "r"(a2), "r"(a3), "r"(b0), "r"(b1));
}

__device__ __forceinline__ void wg_n128_tb(float (&d)[64], uint64_t da, uint64_t db, int sd) {
  asm volatile("{\n.reg .pred p;\nsetp.ne.b32 p, %66, 0;\n"
    "wgmma.mma_async.sync.aligned.m64n128k16.f32.bf16.bf16 {%0, %1, %2, %3, %4, %5, %6, %7, %8, %9, %10, %11, %12, %13, %14, %15, %16, %17, %18, %19, %20, %21, %22, %23, %24, %25, %26, %27, %28, %29, %30, %31, %32, %33, %34, %35, %36, %37, %38, %39, %40, %41, %42, %43, %44, %45, %46, %47, %48, %49, %50, %51, %52, %53, %54, %55, %56, %57, %58, %59, %60, %61, %62, %63}, %64, %65, p, 1, 1, 0, 1;\n}\n"
    : "+f"(d[0]), "+f"(d[1]), "+f"(d[2]), "+f"(d[3]), "+f"(d[4]), "+f"(d[5]), "+f"(d[6]), "+f"(d[7]), "+f"(d[8]), "+f"(d[9]), "+f"(d[10]), "+f"(d[11]), "+f"(d[12]), "+f"(d[13]), "+f"(d[14]), "+f"(d[15]), "+f"(d[16]), "+f"(d[17]), "+f"(d[18]), "+f"(d[19]), "+f"(d[20]), "+f"(d[21]), "+f"(d[22]), "+f"(d[23]), "+f"(d[24]), "+f"(d[25]), "+f"(d[26]), "+f"(d[27]), "+f"(d[28]), "+f"(d[29]), "+f"(d[30]), "+f"(d[31]), "+f"(d[32]), "+f"(d[33]), "+f"(d[34]), "+f"(d[35]), "+f"(d[36]), "+f"(d[37]), "+f"(d[38]), "+f"(d[39]), "+f"(d[40]), "+f"(d[41]), "+f"(d[42]), "+f"(d[43]), "+f"(d[44]), "+f"(d[45]), "+f"(d[46]), "+f"(d[47]), "+f"(d[48]), "+f"(d[49]), "+f"(d[50]), "+f"(d[51]), "+f"(d[52]), "+f"(d[53]), "+f"(d[54]), "+f"(d[55]), "+f"(d[56]), "+f"(d[57]), "+f"(d[58]), "+f"(d[59]), "+f"(d[60]), "+f"(d[61]), "+f"(d[62]), "+f"(d[63])
    : "l"(da), "l"(db), "r"(sd));
}
__device__ __forceinline__ void wg_n144(float (&d)[72], uint64_t da, uint64_t db, int sd) {
  asm volatile("{\n.reg .pred p;\nsetp.ne.b32 p, %74, 0;\n"
    "wgmma.mma_async.sync.aligned.m64n144k16.f32.bf16.bf16 {%0, %1, %2, %3, %4, %5, %6, %7, %8, %9, %10, %11, %12, %13, %14, %15, %16, %17, %18, %19, %20, %21, %22, %23, %24, %25, %26, %27, %28, %29, %30, %31, %32, %33, %34, %35, %36, %37, %38, %39, %40, %41, %42, %43, %44, %45, %46, %47, %48, %49, %50, %51, %52, %53, %54, %55, %56, %57, %58, %59, %60, %61, %62, %63, %64, %65, %66, %67, %68, %69, %70, %71}, %72, %73, p, 1, 1, 0, 0;\n}\n"
    : "+f"(d[0]), "+f"(d[1]), "+f"(d[2]), "+f"(d[3]), "+f"(d[4]), "+f"(d[5]), "+f"(d[6]), "+f"(d[7]), "+f"(d[8]), "+f"(d[9]), "+f"(d[10]), "+f"(d[11]), "+f"(d[12]), "+f"(d[13]), "+f"(d[14]), "+f"(d[15]), "+f"(d[16]), "+f"(d[17]), "+f"(d[18]), "+f"(d[19]), "+f"(d[20]), "+f"(d[21]), "+f"(d[22]), "+f"(d[23]), "+f"(d[24]), "+f"(d[25]), "+f"(d[26]), "+f"(d[27]), "+f"(d[28]), "+f"(d[29]), "+f"(d[30]), "+f"(d[31]), "+f"(d[32]), "+f"(d[33]), "+f"(d[34]), "+f"(d[35]), "+f"(d[36]), "+f"(d[37]), "+f"(d[38]), "+f"(d[39]), "+f"(d[40]), "+f"(d[41]), "+f"(d[42]), "+f"(d[43]), "+f"(d[44]), "+f"(d[45]), "+f"(d[46]), "+f"(d[47]), "+f"(d[48]), "+f"(d[49]), "+f"(d[50]), "+f"(d[51]), "+f"(d[52]), "+f"(d[53]), "+f"(d[54]), "+f"(d[55]), "+f"(d[56]), "+f"(d[57]), "+f"(d[58]), "+f"(d[59]), "+f"(d[60]), "+f"(d[61]), "+f"(d[62]), "+f"(d[63]), "+f"(d[64]), "+f"(d[65]), "+f"(d[66]), "+f"(d[67]), "+f"(d[68]), "+f"(d[69]), "+f"(d[70]), "+f"(d[71])
    : "l"(da), "l"(db), "r"(sd));
}
__device__ __forceinline__ void wg_n160(float (&d)[80], uint64_t da, uint64_t db, int sd) {
  asm volatile("{\n.reg .pred p;\nsetp.ne.b32 p, %82, 0;\n"
    "wgmma.mma_async.sync.aligned.m64n160k16.f32.bf16.bf16 {%0, %1, %2, %3, %4, %5, %6, %7, %8, %9, %10, %11, %12, %13, %14, %15, %16, %17, %18, %19, %20, %21, %22, %23, %24, %25, %26, %27, %28, %29, %30, %31, %32, %33, %34, %35, %36, %37, %38, %39, %40, %41, %42, %43, %44, %45, %46, %47, %48, %49, %50, %51, %52, %53, %54, %55, %56, %57, %58, %59, %60, %61, %62, %63, %64, %65, %66, %67, %68, %69, %70, %71, %72, %73, %74, %75, %76, %77, %78, %79}, %80, %81, p, 1, 1, 0, 0;\n}\n"
    : "+f"(d[0]), "+f"(d[1]), "+f"(d[2]), "+f"(d[3]), "+f"(d[4]), "+f"(d[5]), "+f"(d[6]), "+f"(d[7]), "+f"(d[8]), "+f"(d[9]), "+f"(d[10]), "+f"(d[11]), "+f"(d[12]), "+f"(d[13]), "+f"(d[14]), "+f"(d[15]), "+f"(d[16]), "+f"(d[17]), "+f"(d[18]), "+f"(d[19]), "+f"(d[20]), "+f"(d[21]), "+f"(d[22]), "+f"(d[23]), "+f"(d[24]), "+f"(d[25]), "+f"(d[26]), "+f"(d[27]), "+f"(d[28]), "+f"(d[29]), "+f"(d[30]), "+f"(d[31]), "+f"(d[32]), "+f"(d[33]), "+f"(d[34]), "+f"(d[35]), "+f"(d[36]), "+f"(d[37]), "+f"(d[38]), "+f"(d[39]), "+f"(d[40]), "+f"(d[41]), "+f"(d[42]), "+f"(d[43]), "+f"(d[44]), "+f"(d[45]), "+f"(d[46]), "+f"(d[47]), "+f"(d[48]), "+f"(d[49]), "+f"(d[50]), "+f"(d[51]), "+f"(d[52]), "+f"(d[53]), "+f"(d[54]), "+f"(d[55]), "+f"(d[56]), "+f"(d[57]), "+f"(d[58]), "+f"(d[59]), "+f"(d[60]), "+f"(d[61]), "+f"(d[62]), "+f"(d[63]), "+f"(d[64]), "+f"(d[65]), "+f"(d[66]), "+f"(d[67]), "+f"(d[68]), "+f"(d[69]), "+f"(d[70]), "+f"(d[71]), "+f"(d[72]), "+f"(d[73]), "+f"(d[74]), "+f"(d[75]), "+f"(d[76]), "+f"(d[77]), "+f"(d[78]), "+f"(d[79])
    : "l"(da), "l"(db), "r"(sd));
}
__device__ __forceinline__ void wg_n80(float (&d)[40], uint64_t da, uint64_t db, int sd) {
  asm volatile("{\n.reg .pred p;\nsetp.ne.b32 p, %42, 0;\n"
    "wgmma.mma_async.sync.aligned.m64n80k16.f32.bf16.bf16 {%0, %1, %2, %3, %4, %5, %6, %7, %8, %9, %10, %11, %12, %13, %14, %15, %16, %17, %18, %19, %20, %21, %22, %23, %24, %25, %26, %27, %28, %29, %30, %31, %32, %33, %34, %35, %36, %37, %38, %39}, %40, %41, p, 1, 1, 0, 0;\n}\n"
    : "+f"(d[0]), "+f"(d[1]), "+f"(d[2]), "+f"(d[3]), "+f"(d[4]), "+f"(d[5]), "+f"(d[6]), "+f"(d[7]), "+f"(d[8]), "+f"(d[9]), "+f"(d[10]), "+f"(d[11]), "+f"(d[12]), "+f"(d[13]), "+f"(d[14]), "+f"(d[15]), "+f"(d[16]), "+f"(d[17]), "+f"(d[18]), "+f"(d[19]), "+f"(d[20]), "+f"(d[21]), "+f"(d[22]), "+f"(d[23]), "+f"(d[24]), "+f"(d[25]), "+f"(d[26]), "+f"(d[27]), "+f"(d[28]), "+f"(d[29]), "+f"(d[30]), "+f"(d[31]), "+f"(d[32]), "+f"(d[33]), "+f"(d[34]), "+f"(d[35]), "+f"(d[36]), "+f"(d[37]), "+f"(d[38]), "+f"(d[39])
    : "l"(da), "l"(db), "r"(sd));
}
__device__ __forceinline__ void wg_n24_tatb(float (&d)[12], uint64_t da, uint64_t db, int sd) {
  asm volatile("{\n.reg .pred p;\nsetp.ne.b32 p, %14, 0;\n"
    "wgmma.mma_async.sync.aligned.m64n24k16.f32.bf16.bf16 {%0, %1, %2, %3, %4, %5, %6, %7, %8, %9, %10, %11}, %12, %13, p, 1, 1, 1, 1;\n}\n"
    : "+f"(d[0]), "+f"(d[1]), "+f"(d[2]), "+f"(d[3]), "+f"(d[4]), "+f"(d[5]), "+f"(d[6]), "+f"(d[7]), "+f"(d[8]), "+f"(d[9]), "+f"(d[10]), "+f"(d[11])
    : "l"(da), "l"(db), "r"(sd));
}
__device__ __forceinline__ void wg_n88_rs(float (&d)[44], uint32_t a0, uint32_t a1, uint32_t a2, uint32_t a3, uint64_t db, int sd) {
  asm volatile("{\n.reg .pred p;\nsetp.ne.b32 p, %49, 0;\n"
    "wgmma.mma_async.sync.aligned.m64n88k16.f32.bf16.bf16 {%0, %1, %2, %3, %4, %5, %6, %7, %8, %9, %10, %11, %12, %13, %14, %15, %16, %17, %18, %19, %20, %21, %22, %23, %24, %25, %26, %27, %28, %29, %30, %31, %32, %33, %34, %35, %36, %37, %38, %39, %40, %41, %42, %43}, {%44, %45, %46, %47}, %48, p, 1, 1, 0;\n}\n"
    : "+f"(d[0]), "+f"(d[1]), "+f"(d[2]), "+f"(d[3]), "+f"(d[4]), "+f"(d[5]), "+f"(d[6]), "+f"(d[7]), "+f"(d[8]), "+f"(d[9]), "+f"(d[10]), "+f"(d[11]), "+f"(d[12]), "+f"(d[13]), "+f"(d[14]), "+f"(d[15]), "+f"(d[16]), "+f"(d[17]), "+f"(d[18]), "+f"(d[19]), "+f"(d[20]), "+f"(d[21]), "+f"(d[22]), "+f"(d[23]), "+f"(d[24]), "+f"(d[25]), "+f"(d[26]), "+f"(d[27]), "+f"(d[28]), "+f"(d[29]), "+f"(d[30]), "+f"(d[31]), "+f"(d[32]), "+f"(d[33]), "+f"(d[34]), "+f"(d[35]), "+f"(d[36]), "+f"(d[37]), "+f"(d[38]), "+f"(d[39]), "+f"(d[40]), "+f"(d[41]), "+f"(d[42]), "+f"(d[43])
    : "r"(a0), "r"(a1), "r"(a2), "r"(a3), "l"(db), "r"(sd));
}

struct NoHook { __device__ __forceinline__ void operator()(int) const {} };
template <int NKB, bool RING2 = false, class Issue, class Hook = NoHook>
__device__ __forceinline__ void mainloop(int idx0, int lane, int order_bar, Issue&& issue, Hook&& hook = Hook()) {
  constexpr int NS = RING2 ? NSLOT2 : NSLOT, SB = RING2 ? SLOT2_BYTES : SLOT_BYTES;
  constexpr uint32_t bfull = SBASE + OFF_BAR + (RING2 ? B_FULL2 : B_FULL), bempty = SBASE + OFF_BAR + (RING2 ? B_EMPTY2 : B_EMPTY);
  constexpr int TLO = RING2 ? 30 : 0;
  (void)TLO;
  int slot = idx0 % NS;
  uint32_t ph = (idx0 / NS) & 1;
  int prev = slot;
#pragma unroll 1
  for (int kb = 0; kb < NKB; kb++) {
    mbar_wait(bfull + slot * 8, ph);
    wg_fence();
    issue((SBASE >> 4) + slot * (SB >> 4), kb);
    wg_commit();
    if (kb == NKB - 1 && order_bar >= 0) nb_arrive(order_bar, 256);
    hook(kb);
    wg_wait<1>();
    if (kb > 0 && lane == 0) mbar_arrive(bempty + prev * 8);
    prev = slot;
    if (++slot == NS) { slot = 0; ph ^= 1; }
  }
  wg_wait<0>();
  if (lane == 0) mbar_arrive(bempty + prev * 8);
}

template <int NG, int OFF, int N>
__device__ __forceinline__ void epi_h(const float (&a0)[N], const float2 (&cs)[NG], float2 r0, float2 r1, __nv_bfloat16* hp) {
  const float h0 = 0.5f * r0.x, h1 = 0.5f * r1.x;
#pragma unroll
  for (int q = 0; q < NG / 4; q++) {
    uint32_t w0[4], w1[4];
#pragma unroll
    for (int t = 0; t < 4; t++) {
      const int g = 4 * q + t;
      w0[t] = pack2(silu_half(h0 * fmaf(r0.y, cs[g].x, a0[OFF + 4 * g + 0])), silu_half(h0 * fmaf(r0.y, cs[g].y, a0[OFF + 4 * g + 1])));
      w1[t] = pack2(silu_half(h1 * fmaf(r1.y, cs[g].x, a0[OFF + 4 * g + 2])), silu_half(h1 * fmaf(r1.y, cs[g].y, a0[OFF + 4 * g + 3])));
    }
    *reinterpret_cast<uint4*>(hp + 32 * q) = make_uint4(w0[0], w0[1], w0[2], w0[3]);
    *reinterpret_cast<uint4*>(hp + 8 * FF + 32 * q) = make_uint4(w1[0], w1[1], w1[2], w1[3]);
  }
}

__device__ __forceinline__ float ex2_fma(float x) {
  x = fmaxf(x, -126.0f);
  const float t = x + 12582912.0f;
  const float f = x - (t - 12582912.0f);
  float p = fmaf(0.009570101276040077f, f, 0.05591785907745361f);
  p = fmaf(p, f, 0.240247443318367f);
  p = fmaf(p, f, 0.6931217908859253f);
  p = fmaf(p, f, 0.9999992847442627f);
  return __int_as_float(__float_as_int(p) + (__float_as_int(t) << 23));
}
__device__ __forceinline__ void softmax_exp(const float (&p)[20], float a2, float (&e)[40]) {
  float mx[4], mn[4];
#pragma unroll
  for (int q = 0; q < 4; q++) {
    mx[q] = fmaxf(fmaxf(p[5 * q], p[5 * q + 1]), fmaxf(p[5 * q + 2], fmaxf(p[5 * q + 3], p[5 * q + 4])));
    mn[q] = fminf(fminf(p[5 * q], p[5 * q + 1]), fminf(p[5 * q + 2], fminf(p[5 * q + 3], p[5 * q + 4])));
  }
  const float mxs = -a2 * fmaxf(fmaxf(mx[0], mx[1]), fmaxf(mx[2], mx[3])), mns = a2 * fminf(fminf(mn[0], mn[1]), fminf(mn[2], mn[3]));
#pragma unroll
  for (int f = 0; f < 20; f++) {
    e[f] = ex2(fmaf(a2, p[f], mxs));
    e[20 + f] = ex2(fmaf(-a2, p[f], mns));
  }
}
__device__ __forceinline__ bool split_block() { uint32_t v; asm volatile("mov.u32 %0, %%nwarpid;" : "=r"(v)); return v != 0; }
__device__ __forceinline__ void softmax_norm(const float (&e)[40], uint32_t (&w)[20]) {
  float s[8];
#pragma unroll
  for (int q = 0; q < 8; q++) s[q] = ((e[5 * q] + e[5 * q + 1]) + (e[5 * q + 2] + e[5 * q + 3])) + e[5 * q + 4];
  const float rp = rcp((s[0] + s[1]) + (s[2] + s[3])), rn = rcp((s[4] + s[5]) + (s[6] + s[7]));
#pragma unroll
  for (int t = 0; t < 10; t++) {
    w[t] = pack2(e[2 * t] * rp, e[2 * t + 1] * rp);
    w[10 + t] = pack2(e[20 + 2 * t] * rn, e[20 + 2 * t + 1] * rn);
  }
}

__device__ __forceinline__ void transpose_item(const __nv_bfloat16* src, int st2, int st1, uint8_t* dst) {
  uint32_t v[8];
#pragma unroll
  for (int m = 0; m < 4; m++) { v[2 * m] = ldg32(src + m * st2); v[2 * m + 1] = ldg32(src + m * st2 + st1); }
  *reinterpret_cast<uint4*>(dst) =
      make_uint4(__byte_perm(v[0], v[1], 0x5410), __byte_perm(v[2], v[3], 0x5410), __byte_perm(v[4], v[5], 0x5410), __byte_perm(v[6], v[7], 0x5410));
  *reinterpret_cast<uint4*>(dst + 16) =
      make_uint4(__byte_perm(v[0], v[1], 0x7632), __byte_perm(v[2], v[3], 0x7632), __byte_perm(v[4], v[5], 0x7632), __byte_perm(v[6], v[7], 0x7632));
}

__global__ void __launch_bounds__(384, 1) fused_kernel(const __grid_constant__ Params P) {
  extern __shared__ __align__(1024) uint8_t smem_raw[];
  constexpr uint32_t sbase = SBASE;
  constexpr uint32_t bar = sbase + OFF_BAR;
  constexpr uint32_t stg = sbase + OFF_STG;
  const int tid = threadIdx.x, warp = __shfl_sync(0xffffffffu, tid >> 5, 0), lane = tid & 31;
  const int bid = blockIdx.x;
  const bool helper = (bid >= 112 && bid < 114) || bid >= 130;
  const int work = bid < 112 ? bid : bid - 2;
  const int r = work >> 3, c = work & 7;
  const int li = lane >> 2, lj = lane & 3;

  if (helper) {
    constexpr int NIN = 8, NOUT = 3;
    constexpr uint32_t IN0 = SBASE, OUT0 = SBASE + NIN * 20480, HB = OUT0 + NOUT * 20480;
    constexpr uint32_t H_FULL = HB, H_EMPTY = HB + 64, H_ORDY = HB + 128, H_OFREE = HB + 192;
    const int hs = bid < 114 ? bid - 112 : bid - 128;
    if (tid == 0) {
      TL(1);
      if (smem_u32(smem_raw) != sbase) __trap();
      for (int q = 0; q < NIN; q++) { mbar_init(H_FULL + q * 8, 1); mbar_init(H_EMPTY + q * 8, 10); }
      for (int q = 0; q < NOUT; q++) { mbar_init(H_ORDY + q * 8, 10); mbar_init(H_OFREE + q * 8, 1); }
      asm volatile("fence.mbarrier_init.release.cluster;" ::: "memory");
    }
    __syncthreads();
    if (warp == 10) {
      if (lane == 0) {
#pragma unroll 1
        for (int kbg = 0; kbg < 34; kbg++) {
          const int q = kbg % NIN;
          mbar_wait_trap(H_EMPTY + q * 8, ((kbg / NIN) & 1) ^ 1);
          mbar_expect_tx(H_FULL + q * 8, 20480);
          const bool isw2 = kbg < 24;
          const int row = isw2 ? (kbg < 16 ? 192 * (kbg >> 1) + 64 * (kbg & 1) : 192 * (kbg - 16) + 128) : 64 * (kbg - 24);
          tma2d(IN0 + q * 20480, isw2 ? &P.tm_w2 : &P.tm_wo, 160 * hs, row, H_FULL + q * 8);
        }
      }
    } else if (warp == 11) {
      if (lane == 0) {
#pragma unroll 1
        for (int kbg = 0; kbg < 34; kbg++) {
          const int q = kbg % NOUT;
          mbar_wait_trap(H_ORDY + q * 8, (kbg / NOUT) & 1);
          bulk1d_store(g_wp3 + (hs * 34 + kbg) * 20480, OUT0 + q * 20480, 20480);
          bulk_commit();
          if (kbg > 0) {
            asm volatile("cp.async.bulk.wait_group.read 1;" ::: "memory");
            mbar_arrive(H_OFREE + ((kbg - 1) % NOUT) * 8);
          }
          if (kbg == 16 || kbg == 24) {
            asm volatile("cp.async.bulk.wait_group 1;" ::: "memory");
            flag_add_relaxed(FL_P3W + 2 * hs);
            flag_add_relaxed(FL_P3W + 2 * hs + 1);
            TL(41);
          }
        }
        bulk_wait0();
        flag_add_relaxed(FL_P3W + 2 * hs);
        flag_add_relaxed(FL_P3W + 2 * hs + 1);
        TL(42);
      }
    } else {
      const int kc = tid / 40, rem = tid - kc * 40, j = rem & 3, g = rem >> 2;
      const uint32_t so_w2 = (32 * (kc >> 2) + 2 * (kc & 3)) * 320 + (20 * j + g) * 4;
      const uint32_t so_wo = (8 * kc) * 320 + (20 * j + g) * 4;
      const uint32_t dof = kc * 2560 + (8 * g + 2 * j) * 16;
      const bool odd = g & 1;
      const uint32_t sel0 = odd ? 0x7632u : 0x5410u, sel1 = odd ? 0x5410u : 0x7632u, o0 = odd ? 16u : 0u;
#pragma unroll 1
      for (int kbg = 0; kbg < 34; kbg++) {
        const int qi = kbg % NIN, qo = kbg % NOUT;
        const bool isw2 = kbg < 24;
        const uint32_t a = IN0 + qi * 20480 + (isw2 ? so_w2 : so_wo), st2 = isw2 ? 8 * 320 : 2 * 320;
        mbar_wait_trap(H_FULL + qi * 8, (kbg / NIN) & 1);
        uint32_t v[2][8];
#pragma unroll
        for (int t = 0; t < 2; t++)
#pragma unroll
          for (int m = 0; m < 4; m++) { v[t][2 * m] = lds32(a + t * 40 + m * st2); v[t][2 * m + 1] = lds32(a + t * 40 + m * st2 + 320); }
        mbar_wait_trap(H_OFREE + qo * 8, ((kbg / NOUT) & 1) ^ 1);
#pragma unroll
        for (int t = 0; t < 2; t++) {
          const uint32_t (&u)[8] = v[t];
          const uint32_t out = OUT0 + qo * 20480 + t * 1280 + dof;
          sts128(out + o0, __byte_perm(u[0], u[1], sel0), __byte_perm(u[2], u[3], sel0), __byte_perm(u[4], u[5], sel0), __byte_perm(u[6], u[7], sel0));
          sts128(out + 16 - o0, __byte_perm(u[0], u[1], sel1), __byte_perm(u[2], u[3], sel1), __byte_perm(u[4], u[5], sel1), __byte_perm(u[6], u[7], sel1));
        }
        fence_async_smem();
        __syncwarp();
        if (lane == 0) { mbar_arrive(H_EMPTY + qi * 8); mbar_arrive(H_ORDY + qo * 8); }
      }
    }
    return;
  }

  if (tid == 0) {
    TLG(0); TL(1);
    if (smem_u32(smem_raw) != sbase) __trap();
#pragma unroll
    for (int s = 0; s < NSLOT; s++) { mbar_init(bar + B_FULL + s * 8, 1); mbar_init(bar + B_EMPTY + s * 8, 4); }
    mbar_init(bar + B_CONST, 1);
    mbar_init(bar + B_XF, 1);
    mbar_init(bar + B_PIN, 1);
    mbar_init(bar + B_SDONE, 8);
    mbar_init(bar + B_KVP, 4);
    mbar_init(bar + B_KVS, 8);
    mbar_init(bar + B_QS, 5);
    mbar_init(bar + B_GATE3, 1);
    mbar_init(bar + B_GATE4, 1);
    mbar_init(bar + B_HAP, 4);
    mbar_init(bar + B_HBP, 4);
    mbar_init(bar + B_KVOK, 1);
    mbar_init(bar + B_KVP0, 4);
    mbar_init(bar + B_KVF, 1);
    mbar_init(bar + B_E2E, 4);
#pragma unroll
    for (int q = 0; q < NSLOT2; q++) { mbar_init(bar + B_FULL2 + q * 8, 1); mbar_init(bar + B_EMPTY2 + q * 8, 4); }
#pragma unroll
    for (int q = 0; q < 5; q++) mbar_init(bar + B_GO2 + q * 8, 1);
    asm volatile("fence.mbarrier_init.release.cluster;" ::: "memory");
    TL(10);
    mbar_expect_tx(bar + B_PIN, 3 * 6400 + 3200);
    tma2d(stg + WIN_OFF + 6400, &P.tm_wqkv, 640 + 80 * c, 40 * r, bar + B_PIN);
    tma2d(stg + WIN_OFF + 12800, &P.tm_wqkv, 1280 + 80 * c, 40 * r, bar + B_PIN);
    bulk1d(sbase + OFF_PHI, P.wphi + c * 1600, 3200, bar + B_PIN);
    tma2d(stg + WIN_OFF, &P.tm_wqkv, 80 * c, 40 * r, bar + B_PIN);
#pragma unroll 1
    for (int k = 0; k < 2; k++) {
      mbar_expect_tx(bar + B_FULL + k * 8, 32768);
      tma2d(sbase + k * SLOT_BYTES, &P.tm_x, k * 64, r * 128, bar + B_FULL + k * 8);
      tma3d(sbase + k * SLOT_BYTES + 16384, &P.tm_w1b, 0, k * 64, 3 * c, bar + B_FULL + k * 8);
    }
    asm volatile("cp.async.bulk.prefetch.L2.global [%0], %1;" ::"l"(P.x + (size_t)work * 16 * DM), "r"(20480) : "memory");
    asm volatile("cp.async.bulk.prefetch.L2.global [%0], %1;" ::"l"(P.w1 + (size_t)work * 5 * FF), "r"(15360) : "memory");
    TL(11);
  }
  __syncthreads();

  if (warp < 4) {
    asm volatile("setmaxnreg.dec.sync.aligned.u32 40;");
    if (warp == 0) {
      if (lane == 0) {
        uint32_t s = sbase + 2 * SLOT_BYTES, fb = bar + B_FULL + 16, ph = 1;
        auto acquire = [&](uint32_t bytes, uint32_t period) {
          mbar_wait_trap(fb + (B_EMPTY - B_FULL), ph);
          mbar_expect_tx(fb, bytes);
        };
        auto advance = [&]() {
          s += SLOT_BYTES; fb += 8;
          if (fb == bar + B_FULL + NSLOT * 8) { s = sbase; fb = bar + B_FULL; ph ^= 1; }
        };
        const int row = r * 128;
#pragma unroll 1
        for (int k = 128; k < 640; k += 64) {
          acquire(32768, 0);
          tma2d(s, &P.tm_x, k, row, fb);
          tma3d(s + 16384, &P.tm_w1b, 0, k, 3 * c, fb);
          PTL(192 + k / 64);
          advance();
        }
        TL(2); mbar_wait_trap(bar + B_GO2, 0); fence_async_global(); TL(3);
        {
          const uint8_t* src = g_wkv + c * 204800;
#pragma unroll 1
          for (int k = 0; k < 640; k += 64, src += 20480) {
            acquire(36864, PACE2);
            tma2d(s, &P.tm_x, k, row, fb);
            bulk1d(s + 16384, src, 20480, fb);
            PTL(202 + k / 64);
            advance();
          }
        }
        mbar_wait_trap(bar + B_GO3, 0); fence_async_global();
        {
          const uint8_t* src = g_wqh + c * 184320;
#pragma unroll 1
          for (int k = 0; k < 640; k += 64, src += 18432) {
            acquire(34816, PACE3);
            tma2d(s, &P.tm_x, k, row, fb);
            bulk1d(s + 16384, src, 18432, fb);
            PTL(212 + k / 64);
            advance();
          }
        }
        TL(4); mbar_wait_trap(bar + B_GO4, 0); fence_async_global(); TL(5);
        const uint8_t* src = g_wp3 + (c >> 1) * 34 * 20480;
        const int row3 = row + 64 * (c & 1);
        uint32_t s2 = sbase, f2 = bar + B_FULL2, e2 = bar + B_EMPTY, p2 = 1;
        auto step = [&](const CUtensorMap* tm, int k) {
          mbar_wait_trap(e2, p2);
          mbar_expect_tx(f2, 28672);
          tma2d(s2, tm, k, row3, f2);
          bulk1d(s2 + 8192, src, 20480, f2);
          src += 20480;
          s2 += SLOT2_BYTES; f2 += 8; e2 += 8;
        };
#pragma unroll 1
        for (int j = 0; j < NSLOT2; j++) {
          step(&P.tm_h, 192 * (j >> 1) + 64 * (j & 1));
          PTL(222 + j);
          if (j == 3) e2 -= 8;
        }
        s2 = sbase; f2 = bar + B_FULL2; e2 = bar + B_EMPTY2; p2 = 0;
        auto wrap = [&]() { if (f2 == bar + B_FULL2 + NSLOT2 * 8) { s2 = sbase; f2 = bar + B_FULL2; e2 = bar + B_EMPTY2; p2 ^= 1; } };
#pragma unroll 1
        for (int j = NSLOT2; j < 16; j++) { step(&P.tm_h, 192 * (j >> 1) + 64 * (j & 1)); PTL(222 + j); wrap(); }
        TL(6); mbar_wait_trap(bar + B_GO5, 0); fence_async_global(); TL(7);
#pragma unroll 1
        for (int u = 128; u < FF; u += 192) { step(&P.tm_h, u); PTL(238 + u / 192); wrap(); }
        TL(8); mbar_wait_trap(bar + B_GO6, 0); fence_async_global(); TL(9);
#pragma unroll 1
        for (int k = 0; k < 640; k += 64) { step(&P.tm_o, k); PTL(246 + k / 64); wrap(); }
      }
    } else {
      unsigned ep = 0;
      if (lane == 0) ep = ld_epoch() + 1;
      ep = __shfl_sync(0xffffffffu, ep, 0);
      const int par = ep & 1;
      if (warp == 1) {
        if (lane == 0) {
          mbar_wait_trap(bar + B_KVS, 0);
          bulk1d_store(g_wkv + (c * 80 + 5 * r) * 2560, stg + WOUT_KV, 12800);
          bulk_commit();
          bulk_wait0();
          TL(49);
          flag_add_relaxed(FL_PREP + c);
          TL(32);
        }
        __syncwarp();
        flag_wait8(FL_PREP, ep * 16, lane);
        if (lane == 0) {
          mbar_arrive(bar + B_GO2);
          mbar_wait_trap(bar + B_QS, 0);
          for (int t = 0; t < 5; t++) bulk1d_store(g_wqh + (c * 80 + 5 * r + t) * 2304 + 1024, stg + WOUT_Q + t * 1280, 1280);
          bulk_commit();
          bulk_wait0();
          flag_add(FL_W1T + c);
        }
        __syncwarp();
        flag_wait8(FL_W1T, ep * 16, lane);
        if (lane == 0) {
          mbar_arrive(bar + B_GO3);
        }
        __syncwarp();
        flag_wait8(FL_P3W, 3 * ep - 2, lane);
        if (lane == 0) {
          flag_wait(FL_HA + r, ep * 8);
          mbar_arrive(bar + B_GO4);
          unsigned long long v;
          int it = 0;
          do {
            asm volatile("ld.relaxed.gpu.global.u64 %0, [%1];" : "=l"(v) : "l"(&g_t0[(work >> 4) * 16]) : "memory");
            if (++it > (1 << 21)) __trap();
          } while ((unsigned)(v >> 32) != ep);
          sts32(sbase + OFF_T0, (uint32_t)v);
          mbar_arrive(bar + B_GATE4);
          mbar_wait_trap(bar + B_HBP, 0);
          flag_add(FL_HB + r);
        }
        __syncwarp();
        flag_wait8(FL_P3W, 3 * ep - 1, lane);
        if (lane == 0) {
          flag_wait(FL_HB + r, ep * 8);
          mbar_arrive(bar + B_GO5);
        }
        __syncwarp();
        flag_wait8(FL_P3W, 3 * ep, lane);
        if (lane == 0) {
          flag_wait(FL_O + r, ep * 32);
          mbar_arrive(bar + B_GO6);
          if (work == 0) g_epoch[0] = ep;
        }
      } else {
        if (warp == 2) {
          if (lane < 27) g_cs[par ^ 1][c * 432 + r * 27 + lane] = 0.f;
          for (int q = lane; q < 60; q += 32) reinterpret_cast<float4*>(&g_kv[par ^ 1][c * 3840 + r * 240])[q] = make_float4(0.f, 0.f, 0.f, 0.f);
          if (lane == 0) {
            mbar_wait_trap(bar + B_SDONE, 0);
            bulk1d_store(&g_stats[r * 128 + c * 16], sbase + OFF_ROWC, 128);
            asm volatile("cp.reduce.async.bulk.global.shared::cta.bulk_group.add.f32 [%0], [%1], %2;" ::"l"(&g_cs[par][c * 432]), "r"(sbase + OFF_CS), "r"(1728) : "memory");
            bulk_commit();
            bulk_wait0();
            flag_add_relaxed(FL_STATS + r);
            flag_add_relaxed(FL_CS + c);
            TL(40);
          }
          __syncwarp();
          flag_wait2(FL_CS + c, ep * 16, FL_STATS + r, ep * 8, lane);
          float v[14];
          float2 st[4];
#pragma unroll
          for (int u = 0; u < 14; u++) v[u] = (u < 13 || lane < 16) ? ldcg_f(&g_cs[par][c * 432 + u * 32 + lane]) : 0.f;
#pragma unroll
          for (int u = 0; u < 4; u++) st[u] = ldcg_f2(&g_stats[r * 128 + u * 32 + lane]);
#pragma unroll
          for (int u = 0; u < 14; u++) if (u < 13 || lane < 16) sts32(sbase + OFF_CS + (u * 32 + lane) * 4, __float_as_uint(v[u]));
#pragma unroll
          for (int u = 0; u < 4; u++) sts64(sbase + OFF_ROWC + (u * 32 + lane) * 8, __float_as_uint(st[u].x), __float_as_uint(st[u].y));
          __syncwarp();
          if (lane == 0) {
            mbar_arrive(bar + B_CONST);
            TL(41);
            mbar_wait_trap(bar + B_HAP, 0);
            flag_add(FL_HA + r);
            mbar_wait_trap(bar + B_E2E, 0);
            if (((atomicAdd(&g_flags[(FL_E2D + (work >> 4)) * 32], 1u) + 1) & 15) == 0)
              asm volatile("st.relaxed.gpu.global.u64 [%0], %1;" ::"l"(&g_t0[(work >> 4) * 16]), "l"(((unsigned long long)ep << 32) | (gtime() + T0_DELAY)) : "memory");
            mbar_wait_trap(bar + B_KVP, 0);
            TL(29);
            asm volatile("cp.reduce.async.bulk.global.shared::cta.bulk_group.add.f32 [%0], [%1], %2;" ::"l"(&g_kv[par][c * 3840]), "r"(stg), "r"(15360) : "memory");
            bulk_commit();
            bulk_wait0();
            flag_add_relaxed(FL_KV + c);
            TL(30);
            flag_wait(FL_KV + c, ep * 16);
            mbar_arrive(bar + B_KVOK);
            TL(43);
          }
        } else {
          mbar_wait_trap(bar + B_FULL, 0);
          const __nv_bfloat16* src = P.w1 + (size_t)(40 * r) * FF + 192 * c + 128 + 2 * lane;
          auto put = [&](const uint32_t (&u)[8], int t) {
            uint8_t* dst = g_wqh + (c * 80 + 5 * r + t) * 2304 + lane * 32;
            *reinterpret_cast<uint4*>(dst) =
                make_uint4(__byte_perm(u[0], u[1], 0x5410), __byte_perm(u[2], u[3], 0x5410), __byte_perm(u[4], u[5], 0x5410), __byte_perm(u[6], u[7], 0x5410));
            *reinterpret_cast<uint4*>(dst + 16) =
                make_uint4(__byte_perm(u[0], u[1], 0x7632), __byte_perm(u[2], u[3], 0x7632), __byte_perm(u[4], u[5], 0x7632), __byte_perm(u[6], u[7], 0x7632));
          };
#pragma unroll 1
          for (int t0 = 0; t0 < 5; t0 += 2) {
            uint32_t tv[2][8];
#pragma unroll
            for (int t = 0; t < 2; t++)
#pragma unroll
              for (int m = 0; m < 8; m++) tv[t][m] = (t0 + t < 5) ? ldg32(src + (8 * (t0 + t) + m) * FF) : 0u;
            put(tv[0], t0);
            if (t0 + 1 < 5) put(tv[1], t0 + 1);
          }
          __syncwarp();
          if (lane == 0) { mbar_arrive(bar + B_QS); TL(39); }
        }
      }
    }
  } else {
   asm volatile("setmaxnreg.inc.sync.aligned.u32 232;");
   const int w = warp & 3;
   const int t128 = tid & 127;
   const uint32_t rowc0 = sbase + OFF_ROWC + (16 * w + li) * 8;
   const uint32_t csj = sbase + OFF_CS + lj * 8;
   unsigned ep = 0;
   if (lane == 0) ep = ld_epoch() + 1;
   {
     uint32_t a[9];
     const int p0 = 8 * (li >> 1) + 2 * w + (li & 1);
     const int npass = warp < 8 ? 2 : 1;
     uint4 x[10];
     uint32_t w1v[40];
     mbar_wait(bar + B_PIN, 0);
     ep = __shfl_sync(0xffffffffu, ep, 0);
     if (t128 == 0 && warp >= 8) TL(45);
#pragma unroll 1
     for (int pass = 0; pass < npass; pass++) {
       const int m = pass > 0 ? 0 : (warp < 8 ? 2 : 1);
       if (m == 2) {
         const uint32_t id = (li == 2 * lj) ? 0x00003F80u : (li == 2 * lj + 1) ? 0x3F800000u : 0u;
         a[0] = id; a[1] = 0; a[2] = 0; a[3] = id; a[4] = 0; a[5] = 0; a[6] = 0; a[7] = 0; a[8] = li < 4 ? id : 0u;
       } else {
         const uint32_t ph = sbase + OFF_PHI + (w * 400 + 2 * lj * 20 + li) * 2;
         auto phi2 = [&](int o) -> uint32_t { return lds16(ph + o * 2) | (lds16(ph + o * 2 + 40) << 16); };
         a[0] = phi2(0); a[1] = phi2(8); a[2] = phi2(160); a[3] = phi2(168);
         a[4] = lj < 2 ? phi2(320) : 0u;
         a[5] = lj < 2 ? phi2(328) : 0u;
         a[6] = li < 4 ? phi2(16) : 0u;
         a[7] = li < 4 ? phi2(176) : 0u;
         a[8] = (li < 4 && lj < 2) ? phi2(336) : 0u;
       }
       constexpr bool live = true;
       const uint32_t wa = stg + WIN_OFF + m * 6400 + li * 160 + (w * 20 + 2 * lj) * 2;
       float c0[5][4], c1[5][4];
#pragma unroll
       for (int t = 0; t < 5; t++) {
         const uint32_t b0 = lds32(wa + t * 1280), b1 = lds32(wa + t * 1280 + 16), b2 = lj < 2 ? lds32(wa + t * 1280 + 32) : 0u;
         mma16816_z(c0[t], a[0], a[1], a[2], a[3], b0, b1);
         mma16816_z(c1[t], a[6], 0u, a[7], 0u, b0, b1);
         mma16816(c0[t], a[4], a[5], 0u, 0u, b2, 0u);
         mma16816(c1[t], a[8], 0u, 0u, 0u, b2, 0u);
       }
       const uint32_t op = stg + (m == 0 ? WOUT_Q : WOUT_KV + (m == 2 ? 80 * 16 : 0)) + p0 * 16 + 4 * lj;
       const uint32_t cstride = m == 0 ? 1280 : 2560;
       float s0 = 0.f, s1 = 0.f, s2 = 0.f;
#pragma unroll
       for (int t = 0; t < 5; t++) {
         const uint32_t v0 = pack2(c0[t][0], c0[t][1]), v1 = pack2(c0[t][2], c0[t][3]), v2 = pack2(c1[t][0], c1[t][1]);
         if (live) sts32(op + t * cstride, v0);
         if (live) sts32(op + t * cstride + 32 * 16, v1);
         if (live && li < 4) sts32(op + t * cstride + 64 * 16, v2);
         s0 += bf_lo(v0) + bf_hi(v0); s1 += bf_lo(v1) + bf_hi(v1); s2 += bf_lo(v2) + bf_hi(v2);
       }
       fence_async_smem();
       if (pass == 0) { __syncwarp(); if (lane == 0) mbar_arrive(bar + B_KVS); }
       s0 += __shfl_xor_sync(0xffffffffu, s0, 1); s0 += __shfl_xor_sync(0xffffffffu, s0, 2);
       s1 += __shfl_xor_sync(0xffffffffu, s1, 1); s1 += __shfl_xor_sync(0xffffffffu, s1, 2);
       s2 += __shfl_xor_sync(0xffffffffu, s2, 1); s2 += __shfl_xor_sync(0xffffffffu, s2, 2);
       const uint32_t cp = sbase + OFF_CS + ((m == 0 ? 352 : (m == 1 ? 192 : 272)) + p0) * 4;
       if (lj == 0) { sts32(cp, __float_as_uint(s0)); sts32(cp + 128, __float_as_uint(s1)); if (li < 4) sts32(cp + 256, __float_as_uint(s2)); }
       fence_async_smem();
       if (t128 == 0) { if (warp >= 8) TL(46); else if (pass) TL(47); }
       if (pass == 0 && warp >= 8) {
           const __nv_bfloat16* xp = P.x + (size_t)(r * 128 + c * 16 + 4 * w + (lane >> 3)) * DM + (lane & 7) * 8;
#pragma unroll
           for (int k = 0; k < 10; k++) x[k] = ldg128(xp + k * 64);
           if (t128 < 96) {
             const __nv_bfloat16* wp = P.w1 + (size_t)(40 * r) * FF + 192 * c + 2 * t128;
#pragma unroll
             for (int k = 0; k < 40; k++) w1v[k] = ldg32(wp + k * FF);
           }
       } else if (pass) {
         __syncwarp();
         if (lane == 0) { mbar_arrive(bar + B_QS); mbar_arrive(bar + B_SDONE); }
       }
     }
     if (warp >= 8) {
       const int q = 4 * w + (lane >> 3);
      auto sum2 = [](uint32_t v) { return bf_lo(v) + bf_hi(v); };
      float sx = 0.f;
#pragma unroll
      for (int k = 0; k < 10; k++) sx += (sum2(x[k].x) + sum2(x[k].y)) + (sum2(x[k].z) + sum2(x[k].w));
#pragma unroll
      for (int o = 4; o; o >>= 1) sx += __shfl_xor_sync(0xffffffffu, sx, o);
      const float mean = sx * (1.0f / DM);
      auto sq2 = [&](uint32_t v) { const float a = bf_lo(v) - mean, b = bf_hi(v) - mean; return fmaf(a, a, b * b); };
      float ss = 0.f;
#pragma unroll
      for (int k = 0; k < 10; k++) ss += (sq2(x[k].x) + sq2(x[k].y)) + (sq2(x[k].z) + sq2(x[k].w));
#pragma unroll
      for (int o = 4; o; o >>= 1) ss += __shfl_xor_sync(0xffffffffu, ss, o);
      const float var = bf_round(ss * (1.0f / DM));
      const float den = bf_round(sqrt_fast(bf_round(var + 1e-5f)));
      if ((lane & 7) == 0) sts64(sbase + OFF_ROWC + q * 8, __float_as_uint(rcp(den)), __float_as_uint(-bf_round(mean)));
      if (t128 < 96) {
        float t0 = 0.f, t1 = 0.f;
#pragma unroll
        for (int k = 0; k < 40; k++) { t0 += bf_lo(w1v[k]); t1 += bf_hi(w1v[k]); }
        sts64(sbase + OFF_CS + 2 * t128 * 4, __float_as_uint(t0), __float_as_uint(t1));
      }
      fence_async_smem();
      __syncwarp();
      if (lane == 0) mbar_arrive(bar + B_SDONE);
      if (t128 == 0) TL(14);
     }
   }
   if (warp < 8) {
    {
      float acc[2][64];
      mainloop<10>(0, lane, NB_A2B, [&](uint32_t s, int kb) {
        static_for<0, 4>([&](auto KS) {
          constexpr int ks = KS.value;
          const uint64_t db = desc_sw128<16384 + ks * 2048, 8192>(s);
          wg_n128_tb(acc[0], desc_sw128<ks * 32>(s), db, ks ? 1 : kb);
          wg_n128_tb(acc[1], desc_sw128<8192 + ks * 32>(s), db, ks ? 1 : kb);
        });
      });
      reg_fence(acc[0]); reg_fence(acc[1]);
      if (t128 == 0) TL(16);
      mbar_wait(bar + B_CONST, 0);
      if (t128 == 0) TL(17);
      float2 cs[16];
#pragma unroll
      for (int g = 0; g < 16; g++) cs[g] = lds_f2(csj + 32 * g);
      __nv_bfloat16* hp = g_h + (size_t)(r * 128 + 16 * w + li) * FF + 192 * c + 8 * lj;
#pragma unroll 1
      for (int mb = 0; mb < 2; mb++) {
        epi_h<16, 0>(acc[0], cs, lds_f2(rowc0 + mb * 512), lds_f2(rowc0 + mb * 512 + 64), hp + mb * 64 * FF);
#pragma unroll
        for (int i = 0; i < 64; i++) acc[0][i] = acc[1][i];
        if (t128 == 0) TL(56 + mb);
      }
      __syncwarp();
      if (lane == 0) mbar_arrive(bar + B_HAP);
      if (t128 == 0) TL(18);
    }
    {
      float acc[2][72];
      nb_sync(NB_B2A, 256);
      if (t128 == 0) TL(19);
      mainloop<10>(20, lane, NB_A2B, [&](uint32_t s, int kb) {
        static_for<0, 4>([&](auto KS) {
          constexpr int ks = KS.value;
          const uint64_t db = desc_nosw<16384 + ks * 4608, 2304, 128>(s);
          wg_n144(acc[0], desc_sw128<ks * 32>(s), db, ks ? 1 : kb);
          wg_n144(acc[1], desc_sw128<8192 + ks * 32>(s), db, ks ? 1 : kb);
        });
      });
      reg_fence(acc[0]); reg_fence(acc[1]);
      if (t128 == 0) TL(20);
      {
        float2 cs[8];
#pragma unroll
        for (int g = 0; g < 8; g++) cs[g] = lds_f2(csj + 128 * 4 + 32 * g);
        __nv_bfloat16* hp = g_h + (size_t)(r * 128 + 16 * w + li) * FF + 192 * c + 128 + 8 * lj;
#pragma unroll 1
        for (int mb = 0; mb < 2; mb++) {
          epi_h<8, 0>(acc[0], cs, lds_f2(rowc0 + mb * 512), lds_f2(rowc0 + mb * 512 + 64), hp + mb * 64 * FF);
#pragma unroll
          for (int i = 0; i < 32; i++) acc[0][i] = acc[1][i];
        }
      }
      __syncwarp();
      if (lane == 0) mbar_arrive(bar + B_HBP);
      if (t128 == 0) TL(21);
      float bk[4][20];
      {
        float2 cq[10];
#pragma unroll
        for (int g = 0; g < 10; g++) cq[g] = lds_f2(csj + 352 * 4 + 32 * g);
#pragma unroll
        for (int t = 0; t < 4; t++) {
          const float nm = lds_f2(rowc0 + (t >> 1) * 512 + (t & 1) * 64).y;
#pragma unroll
          for (int g = 0; g < 10; g++) {
            bk[t][2 * g] = fmaf(nm, cq[g].x, acc[t >> 1][32 + 4 * g + 2 * (t & 1)]);
            bk[t][2 * g + 1] = fmaf(nm, cq[g].y, acc[t >> 1][32 + 4 * g + 2 * (t & 1) + 1]);
          }
        }
      }
#pragma unroll 1
      for (int mb = 0; mb < 2; mb++) {
        float e0[40], e1[40];
        softmax_exp(bk[0], lds_f2(rowc0 + mb * 512).x * LOG2E, e0);
        softmax_exp(bk[1], lds_f2(rowc0 + mb * 512 + 64).x * LOG2E, e1);
#pragma unroll
        for (int i = 0; i < 20; i++) { bk[0][i] = bk[2][i]; bk[1][i] = bk[3][i]; }
        if (split_block()) {
          uint32_t f0[20], f1[20];
          softmax_norm(e0, f0);
          softmax_norm(e1, f1);
#pragma unroll
          for (int i = 0; i < 20; i++) { bk[2][i] = __uint_as_float(f0[i]); bk[3][i] = __uint_as_float(f1[i]); }
        }
      }
      if (t128 == 0) TL(52);
      {
        mbar_wait(bar + B_KVOK, 0);
            if (t128 == 0) TL(22);
            int tl_;
            asm volatile("mov.u32 %0, %1;" : "=r"(tl_) : "r"(t128));
            float4 v0[4], v1[4];
#pragma unroll
            for (int u = 0; u < 4; u++) {
              const int item = tl_ + 128 * u, t = item >> 2, kc = t / 6, q = t - kc * 6;
              if (item < 480) {
                const float* sp = &g_kv[ep & 1][((4 * c + (item & 3)) * 40 + 2 * kc) * 24 + 4 * q];
                v0[u] = ldcg_f4(sp); v1[u] = ldcg_f4(sp + 24);
              }
            }
            const int hj = tl_ & 3;
            const bool odd = (tl_ >> 2) & 1;
            const uint32_t m0 = hj == 0 ? ~0u : 0u, m1 = hj == 1 ? ~0u : 0u, m2 = hj == 2 ? ~0u : 0u, m3 = hj == 3 ? ~0u : 0u;
            const uint32_t o0 = odd ? 16u : 0u, o1 = 16u - o0;
#pragma unroll
            for (int u = 0; u < 4; u++) {
              const int item = tl_ + 128 * u, t = item >> 2, kc = t / 6, q = t - kc * 6;
              if (item < 480) {
                const uint32_t dst = stg + kc * BKV_LBO + hj * 32 + 2 * q * 128;
                uint32_t w0 = pack2(v0[u].x, v1[u].x), w1 = pack2(v0[u].y, v1[u].y);
                const uint32_t w2 = pack2(v0[u].z, v1[u].z), w3 = pack2(v0[u].w, v1[u].w);
                if (q == 5) w1 = 0u;
                const uint32_t a0 = odd ? w1 : w0, a1 = odd ? w0 : w1, b0 = odd ? w3 : w2, b1 = odd ? w2 : w3;
                sts128(dst + o0, a0 & m0, a0 & m1, a0 & m2, a0 & m3);
                sts128(dst + o1, a1 & m0, a1 & m1, a1 & m2, a1 & m3);
                if (q < 5) {
                  sts128(dst + 128 + o0, b0 & m0, b0 & m1, b0 & m2, b0 & m3);
                  sts128(dst + 128 + o1, b1 & m0, b1 & m1, b1 & m2, b1 & m3);
                }
              }
            }
            fence_async_smem();
            nb_sync(NB_A, 128);
            if (t128 == 0) TL(44);
      }
      {
        float ao[2][44];
        wg_fence();
        static_for<0, 20>([&](auto I) {
          constexpr int mb = I.value / 10, ks = I.value % 10;
          wg_n88_rs(ao[mb], __float_as_uint(bk[2 * mb][2 * ks]), __float_as_uint(bk[2 * mb + 1][2 * ks]), __float_as_uint(bk[2 * mb][2 * ks + 1]),
                    __float_as_uint(bk[2 * mb + 1][2 * ks + 1]), desc_nosw<2 * ks * BKV_LBO, BKV_LBO, 128>(stg >> 4), ks != 0);
        });
        wg_commit();
        wg_wait<0>();
        reg_fence(ao[0]); reg_fence(ao[1]);
        if (t128 == 0) TL(53);
        nb_sync(NB_A, 128);
        const uint32_t ost = stg + w * 5120;
#pragma unroll
        for (int mb = 0; mb < 2; mb++) {
          const float i0 = rcp(ao[mb][40] + 1e-6f), i1 = rcp(ao[mb][42] + 1e-6f);
          const uint32_t oa = ost + mb * 2560 + li * 160 + lj * 40;
#pragma unroll
          for (int m = 0; m < 5; m++) {
            sts64(oa + m * 8, pack2(ao[mb][8 * m] * i0, ao[mb][8 * m + 1] * i0), pack2(ao[mb][8 * m + 4] * i0, ao[mb][8 * m + 5] * i0));
            sts64(oa + 8 * 160 + m * 8, pack2(ao[mb][8 * m + 2] * i1, ao[mb][8 * m + 3] * i1), pack2(ao[mb][8 * m + 6] * i1, ao[mb][8 * m + 7] * i1));
          }
        }
        fence_async_smem();
        __syncwarp();
        if (lane == 0) {
          tma2d_store(&P.tm_ost, 80 * c, r * 128 + 16 * w, ost);
          tma2d_store(&P.tm_ost, 80 * c, r * 128 + 64 + 16 * w, ost + 2560);
          bulk_commit();
        }
      }
      if (t128 == 0) TL(54);
      if (lane == 0) { bulk_wait0(); if (t128 == 0) TL(55); flag_add_relaxed(FL_O + r); }
      nb_sync(NB_A, 128);
      if (t128 == 0) {
        TL(23);
        mbar_expect_tx(bar + B_XF, 20480);
        tma2d(stg + XO_OFF, &P.tm_xt, 160 * (c >> 1), r * 128 + 64 * (c & 1), bar + B_XF);
      }
      nb_arrive(NB_STG, 256);
    }
    {
      float acc[80];
      nb_sync(NB_B2A, 256);
      if (t128 == 0) TL(24);
      mainloop<10, true>(24, lane, -1, [&](uint32_t s, int kb) {
        static_for<0, 4>([&](auto KS) {
          constexpr int ks = KS.value;
          wg_n160(acc, desc_sw128<ks * 32>(s), desc_nosw<8192 + ks * 5120, 2560, 128>(s), ks ? 1 : kb);
        });
      });
      reg_fence(acc);
      if (t128 == 0) TL(25);
      mbar_wait(bar + B_XF, 0);
      nb_sync(NB_G, 256);
      const uint32_t xo = stg + XO_OFF + 16 * w * 320;
#pragma unroll 1
      for (int rs = 0; rs < 2; rs++) {
        const uint32_t xa = xo + (li + 8 * rs) * 320 + lj * 80;
#pragma unroll
        for (int q = 0; q < 5; q++) {
          const uint4 gv = lds128(stg + (rs * 5 + q) * 2048 + t128 * 16), xv = lds128(xa + q * 16);
          const uint32_t gq[4] = {gv.x, gv.y, gv.z, gv.w}, xq[4] = {xv.x, xv.y, xv.z, xv.w};
          uint32_t o[4];
#pragma unroll
          for (int t = 0; t < 4; t++) {
            const int g = 4 * q + t;
            o[t] = pack2(fmaf(acc[4 * g], bf_lo(gq[t]), bf_lo(xq[t])), fmaf(acc[4 * g + 1], bf_hi(gq[t]), bf_hi(xq[t])));
          }
          sts128(xa + q * 16, o[0], o[1], o[2], o[3]);
        }
#pragma unroll
        for (int g = 0; g < 20; g++) { acc[4 * g] = acc[4 * g + 2]; acc[4 * g + 1] = acc[4 * g + 3]; }
      }
      fence_async_smem();
      __syncwarp();
      if (lane == 0) { tma2d_store(&P.tm_out, 160 * (c >> 1), r * 128 + 64 * (c & 1) + 16 * w, xo); bulk_commit(); }
      if (lane == 0) bulk_wait_read0();
      if (t128 == 0) { TL(26); TLG(27); }
    }
   } else {
    {
      float acc[2][80];
      nb_sync(NB_A2B, 256);
      if (t128 == 0) TL(33);
      mainloop<10>(10, lane, T3_GO < 0 ? NB_B2A : -1, [&](uint32_t s, int kb) {
        static_for<0, 4>([&](auto KS) {
          constexpr int ks = KS.value;
          const uint64_t db = desc_nosw<16384 + ks * 5120, 2560, 128>(s);
          wg_n160(acc[0], desc_sw128<ks * 32>(s), db, ks ? 1 : kb);
          wg_n160(acc[1], desc_sw128<8192 + ks * 32>(s), db, ks ? 1 : kb);
        });
      });
      reg_fence(acc[0]); reg_fence(acc[1]);
      if (t128 == 0) TL(34);
      mbar_wait(bar + B_CONST, 0);
      mbar_wait(bar + B_GO3, 0);
      uint32_t vp[4][10];
      {
        float2 cv[10];
#pragma unroll
        for (int g = 0; g < 10; g++) cv[g] = lds_f2(csj + 272 * 4 + 32 * g);
#pragma unroll
        for (int t = 0; t < 4; t++) {
          const float2 rc = lds_f2(rowc0 + (t >> 1) * 512 + (t & 1) * 64);
#pragma unroll
          for (int g = 0; g < 10; g++)
            vp[t][g] = pack2(rc.x * fmaf(rc.y, cv[g].x, acc[t >> 1][40 + 4 * g + 2 * (t & 1)]), rc.x * fmaf(rc.y, cv[g].y, acc[t >> 1][40 + 4 * g + 2 * (t & 1) + 1]));
        }
      }
      float bk[4][20];
      {
        float2 ck[10];
#pragma unroll
        for (int g = 0; g < 10; g++) ck[g] = lds_f2(csj + 192 * 4 + 32 * g);
#pragma unroll
        for (int t = 0; t < 4; t++) {
          const float nm = lds_f2(rowc0 + (t >> 1) * 512 + (t & 1) * 64).y;
#pragma unroll
          for (int g = 0; g < 10; g++) {
            bk[t][2 * g] = fmaf(nm, ck[g].x, acc[t >> 1][4 * g + 2 * (t & 1)]);
            bk[t][2 * g + 1] = fmaf(nm, ck[g].y, acc[t >> 1][4 * g + 2 * (t & 1) + 1]);
          }
        }
      }
      if (t128 == 0) TL(28);
      float kvd[4][12];
#pragma unroll 1
      for (int mb = 0; mb < 2; mb++) {
        float e0[40], e1[40];
        softmax_exp(bk[0], lds_f2(rowc0 + mb * 512).x * LOG2E, e0);
        softmax_exp(bk[1], lds_f2(rowc0 + mb * 512 + 64).x * LOG2E, e1);
#pragma unroll
        for (int i = 0; i < 20; i++) { bk[0][i] = bk[2][i]; bk[1][i] = bk[3][i]; }
        if (t128 == 0) TL(58 + 2 * mb);
        if (mb == T3_GO) nb_arrive(NB_B2A, 256);
        if (mb == 1 && lane == 0) mbar_arrive(bar + B_E2E);
        wg_wait<0>();
        nb_sync(NB_B, 128);
        if (split_block()) {
          uint32_t f[2][20];
          softmax_norm(e0, f[0]);
          softmax_norm(e1, f[1]);
#pragma unroll
          for (int rs = 0; rs < 2; rs++) {
            const int kg = 2 * w + rs;
            const uint32_t pa = stg + lj * PHI_HS + kg * 128 + li * 16;
#pragma unroll
            for (int b = 0; b < 5; b++) sts128(pa + b * 1024, f[rs][4 * b], f[rs][4 * b + 1], f[rs][4 * b + 2], f[rs][4 * b + 3]);
            const uint32_t va = stg + V_OFF + lj * V_HS + kg * 128 + li * 16;
            sts128(va, vp[rs][0], vp[rs][1], vp[rs][2], vp[rs][3]);
            sts128(va + 1024, vp[rs][4], vp[rs][5], vp[rs][6], vp[rs][7]);
            sts128(va + 2048, vp[rs][8], vp[rs][9], 0x00003F80u, 0u);
          }
        }
#pragma unroll
        for (int i = 0; i < 10; i++) { vp[0][i] = vp[2][i]; vp[1][i] = vp[3][i]; }
        if (t128 == 0) TL(59 + 2 * mb);
        fence_async_smem();
        nb_sync(NB_B, 128);
        wg_fence();
        static_for<0, 16>([&](auto I) {
          constexpr int hh_ = I.value & 3, ks = I.value >> 2;
          wg_n24_tatb(kvd[hh_], desc_nosw<hh_ * PHI_HS + ks * 256, 128, 1024>(stg >> 4), desc_nosw<V_OFF + hh_ * V_HS + ks * 256, 128, 1024>(stg >> 4), ks ? 1 : mb);
        });
        wg_commit();
        if (t128 == 0) TL(62 + mb);
      }
      wg_wait<0>();
#pragma unroll
      for (int hh_ = 0; hh_ < 4; hh_++) reg_fence(kvd[hh_]);
      nb_sync(NB_B, 128);
#pragma unroll
      for (int rs = 0; rs < 2; rs++) {
        const int fr = 16 * w + li + 8 * rs;
        if (fr < 40) {
#pragma unroll
          for (int hh_ = 0; hh_ < 4; hh_++)
#pragma unroll
            for (int g = 0; g < 3; g++)
              sts64(stg + ((hh_ * 40 + fr) * 24 + 8 * g + 2 * lj) * 4, __float_as_uint(kvd[hh_][4 * g + 2 * rs]), __float_as_uint(kvd[hh_][4 * g + 2 * rs + 1]));
        }
      }
      fence_async_smem();
      __syncwarp();
      if (lane == 0) mbar_arrive(bar + B_KVP);
      if (t128 == 0) TL(35);
    }
    {
      float acc[80];
      mbar_wait(bar + B_GATE4, 0);
      nb_sync(NB_A2B, 256);
      wait_until(lds32(sbase + OFF_T0));
      if (t128 == 0) TL(36);
      mainloop<24, true>(0, lane, NB_B2A, [&](uint32_t s, int kb) {
        static_for<0, 4>([&](auto KS) {
          constexpr int ks = KS.value;
          wg_n160(acc, desc_sw128<ks * 32>(s), desc_nosw<8192 + ks * 5120, 2560, 128>(s), ks ? 1 : kb);
        });
      });
      reg_fence(acc);
      if (t128 == 0) TL(37);
      uint32_t gw[40];
#pragma unroll
      for (int rs = 0; rs < 2; rs++)
#pragma unroll
        for (int g = 0; g < 20; g++) gw[rs * 20 + g] = pack2(silu_half(0.5f * acc[4 * g + 2 * rs]), silu_half(0.5f * acc[4 * g + 2 * rs + 1]));
      nb_sync(NB_STG, 256);
#pragma unroll
      for (int q = 0; q < 10; q++) sts128(stg + q * 2048 + t128 * 16, gw[4 * q], gw[4 * q + 1], gw[4 * q + 2], gw[4 * q + 3]);
      nb_arrive(NB_G, 256);
      if (t128 == 0) TL(38);
    }
   }
  }
}

typedef CUresult (*EncodeFn)(CUtensorMap*, CUtensorMapDataType, cuuint32_t, void*, const cuuint64_t*, const cuuint64_t*, const cuuint32_t*, const cuuint32_t*,
                             CUtensorMapInterleave, CUtensorMapSwizzle, CUtensorMapL2promotion, CUtensorMapFloatOOBfill);

static void encode2d(EncodeFn enc, CUtensorMap* tm, const void* base, uint64_t cols, uint64_t rows, uint32_t bc, uint32_t br, bool swz) {
  cuuint64_t gd[2] = {cols, rows};
  cuuint64_t gs[1] = {cols * 2};
  cuuint32_t bx[2] = {bc, br};
  cuuint32_t es[2] = {1, 1};
  enc(tm, CU_TENSOR_MAP_DATA_TYPE_BFLOAT16, 2, const_cast<void*>(base), gd, gs, bx, es, CU_TENSOR_MAP_INTERLEAVE_NONE,
      swz ? CU_TENSOR_MAP_SWIZZLE_128B : CU_TENSOR_MAP_SWIZZLE_NONE, CU_TENSOR_MAP_L2_PROMOTION_L2_128B, CU_TENSOR_MAP_FLOAT_OOB_FILL_NONE);
}

}

extern "C" void kernel_launch(void* const* d_in, const int* in_sizes, int n_in, void* d_out, int out_size) {
  using namespace hh;
  (void)in_sizes; (void)n_in; (void)out_size;
  static EncodeFn enc = nullptr;
  static void *p_h = nullptr, *p_o = nullptr;
  if (!enc) {
    void* fn = nullptr;
    cudaDriverEntryPointQueryResult qr;
    cudaGetDriverEntryPoint("cuTensorMapEncodeTiled", &fn, cudaEnableDefault, &qr);
    enc = (EncodeFn)fn;
    cudaGetSymbolAddress(&p_h, g_h);
    cudaGetSymbolAddress(&p_o, g_o);
    cudaFuncSetAttribute(fused_kernel, cudaFuncAttributeMaxDynamicSharedMemorySize, SMEM_ALLOC);
  }
  Params P;
  P.x = (const __nv_bfloat16*)d_in[0];
  P.wqkv = (const __nv_bfloat16*)d_in[1];
  P.wphi = (const __nv_bfloat16*)d_in[2];
  P.wo = (const __nv_bfloat16*)d_in[3];
  P.w1 = (const __nv_bfloat16*)d_in[5];
  P.w2 = (const __nv_bfloat16*)d_in[6];
  encode2d(enc, &P.tm_x, P.x, DM, SEQ, 64, 128, true);
  encode2d(enc, &P.tm_h, p_h, FF, SEQ, 64, 64, true);
  encode2d(enc, &P.tm_o, p_o, DM, SEQ, 64, 64, true);
  encode2d(enc, &P.tm_xt, P.x, DM, SEQ, 160, 64, false);
  encode2d(enc, &P.tm_ost, p_o, DM, SEQ, 80, 16, false);
  encode2d(enc, &P.tm_out, d_out, DM, SEQ, 160, 16, false);
  encode2d(enc, &P.tm_wqkv, P.wqkv, 1920, DM, 80, 40, false);
  encode2d(enc, &P.tm_w2, P.w2, DM, FF, 160, 64, false);
  encode2d(enc, &P.tm_wo, P.wo, DM, DM, 160, 64, false);
  {
    cuuint64_t gd[3] = {64, DM, FF / 64};
    cuuint64_t gs[2] = {FF * 2, 128};
    cuuint32_t bx[3] = {64, 64, 2};
    cuuint32_t es[3] = {1, 1, 1};
    enc(&P.tm_w1b, CU_TENSOR_MAP_DATA_TYPE_BFLOAT16, 3, const_cast<__nv_bfloat16*>(P.w1), gd, gs, bx, es, CU_TENSOR_MAP_INTERLEAVE_NONE,
        CU_TENSOR_MAP_SWIZZLE_128B, CU_TENSOR_MAP_L2_PROMOTION_L2_128B, CU_TENSOR_MAP_FLOAT_OOB_FILL_NONE);
  }
  fused_kernel<<<NGRID, 384, SMEM_ALLOC, cudaStreamPerThread>>>(P);
}
```

```cpp
#include <cuda_runtime.h>
#include <cuda_bf16.h>
#include <cuda.h>
#include <stdint.h>
#include <type_traits>

namespace hh {

constexpr int SEQ = 2048, DM = 640, FF = 1536;
constexpr int NCTA = 128;
constexpr int NGRID = 132;
constexpr int NSLOT = 5;
constexpr int SLOT_BYTES = 36864;
constexpr int OFF_STG = NSLOT * SLOT_BYTES;
constexpr int STG_BYTES = 40960;
constexpr int OFF_CS = OFF_STG + STG_BYTES;
constexpr int OFF_ROWC = OFF_CS + 1728;
constexpr int OFF_BAR = OFF_ROWC + 1024;
constexpr int OFF_PHI = OFF_BAR + 384;
constexpr int OFF_T0 = OFF_PHI + 3200;
constexpr int SMEM_USED_BASE = OFF_T0 + 16;
constexpr int SMEM_USED = SMEM_USED_BASE;
constexpr int SMEM_ALLOC = SMEM_USED;
constexpr int B_FULL = 0, B_EMPTY = 40, B_CONST = 80, B_XF = 104, B_PIN = 112, B_SDONE = 120;
constexpr int B_GO2 = 128, B_GO3 = 136, B_GO4 = 144, B_GO5 = 152, B_GO6 = 160, B_KVP = 168, B_KVS = 176, B_QS = 184, B_GATE3 = 200, B_GATE4 = 208, B_HAP = 216, B_HBP = 224, B_KVOK = 232, B_GATE1 = 240, B_GATE2 = 248, B_E2E = 96, B_T1E = 192, B_GO6W = 88;
constexpr int NSLOT2 = 6, SLOT2_BYTES = 28672, B_FULL2 = 256, B_EMPTY2 = 304;
constexpr int WIN_OFF = 0, WOUT_KV = 19200, WOUT_Q = 32000;
constexpr int PHI_HS = 5152, V_OFF = 4 * PHI_HS, V_HS = 3104;
constexpr int BKV_LBO = 1408, OST_OFF = 28160;
constexpr int KVRAW_OFF = 25600;
constexpr int XO_OFF = 20480;
enum { FL_STATS = 0, FL_PREP = 16, FL_P3W = 24, FL_HA = 32, FL_HB = 48, FL_KV = 64, FL_O = 72, FL_CS = 88, FL_W1T = 96, FL_E2D = 104, FL_E1D = 120, FL_TG = 136, FL_N = 160 };
enum { NB_A = 1, NB_B = 2, NB_A2B = 3, NB_B2A = 4, NB_STG = 5, NB_G = 6, NB_AUX = 7 };

#define EARLY_TEST 1
#define T3_GO -1
#define T0_DELAY 900
#define T4_LEAD 256
#define T4_PACE 180
#define PACE2 320
#define PACE3 288
#define PACE4 160
constexpr float LOG2E = 1.4426950408889634f;
constexpr uint32_t SBASE = 1024;

__device__ __align__(1024) uint8_t g_wkv[8 * 10 * 20480];
__device__ __align__(1024) uint8_t g_wqh[8 * 80 * 2304];
__device__ __align__(1024) uint8_t g_wp3[8 * 34 * 10240];
__device__ __align__(1024) __nv_bfloat16 g_h[SEQ * FF];
__device__ __align__(1024) __nv_bfloat16 g_o[SEQ * DM];
__device__ __align__(128) float2 g_stats[SEQ];
__device__ __align__(128) float g_cs[2][8 * 432];
__device__ __align__(128) float g_kv[2][32 * 24 * 40];
__device__ __align__(128) unsigned g_flags[FL_N * 32];
__device__ __align__(128) unsigned g_epoch[32];
__device__ __align__(128) unsigned long long g_t0[3 * 8 * 16];
#define TL(slot) do {} while (0)
#define TLG(slot) do {} while (0)
#define PTL(slot) do {} while (0)

struct Params {
  CUtensorMap tm_x;
  CUtensorMap tm_h;
  CUtensorMap tm_o;
  CUtensorMap tm_xt;
  CUtensorMap tm_ost;
  CUtensorMap tm_out;
  CUtensorMap tm_wqkv;
  CUtensorMap tm_w2;
  CUtensorMap tm_wo;
  CUtensorMap tm_w1b;
  const __nv_bfloat16* x;
  const __nv_bfloat16* wqkv;
  const __nv_bfloat16* wphi;
  const __nv_bfloat16* wo;
  const __nv_bfloat16* w1;
  const __nv_bfloat16* w2;
  __nv_bfloat16* out;
};

__device__ __forceinline__ uint32_t smem_u32(const void* p) { return (uint32_t)__cvta_generic_to_shared(p); }
__device__ __forceinline__ void mbar_init(uint32_t bar, uint32_t cnt) { asm volatile("mbarrier.init.shared::cta.b64 [%0], %1;" ::"r"(bar), "r"(cnt) : "memory"); }
__device__ __forceinline__ void mbar_expect_tx(uint32_t bar, uint32_t bytes) { asm volatile("mbarrier.arrive.expect_tx.shared::cta.b64 _, [%0], %1;" ::"r"(bar), "r"(bytes) : "memory"); }
__device__ __forceinline__ void mbar_arrive(uint32_t bar) { asm volatile("mbarrier.arrive.shared::cta.b64 _, [%0];" ::"r"(bar) : "memory"); }
__device__ __forceinline__ void mbar_wait(uint32_t bar, uint32_t parity) {
  uint32_t ok;
  int it = 0;
  do {
    asm volatile("{\n.reg .pred p;\nmbarrier.try_wait.parity.shared::cta.b64 p, [%1], %2;\nselp.u32 %0, 1, 0, p;\n}" : "=r"(ok) : "r"(bar), "r"(parity) : "memory");
  } while (!ok && ++it < (1 << 17));
}
__device__ __forceinline__ bool mbar_test(uint32_t bar, uint32_t parity) {
  uint32_t ok;
  asm volatile("{\n.reg .pred p;\nmbarrier.test_wait.parity.shared::cta.b64 p, [%1], %2;\nselp.u32 %0, 1, 0, p;\n}" : "=r"(ok) : "r"(bar), "r"(parity) : "memory");
  return ok;
}
__device__ __forceinline__ void mbar_wait_trap(uint32_t bar, uint32_t parity) {
  uint32_t ok;
  int it = 0;
  do {
    asm volatile("{\n.reg .pred p;\nmbarrier.try_wait.parity.shared::cta.b64 p, [%1], %2;\nselp.u32 %0, 1, 0, p;\n}" : "=r"(ok) : "r"(bar), "r"(parity) : "memory");
    if (!ok && ++it > (1 << 20)) __trap();
  } while (!ok);
}
__device__ __forceinline__ void tma2d(uint32_t dst, const CUtensorMap* tm, int c0, int c1, uint32_t bar) {
  asm volatile("cp.async.bulk.tensor.2d.shared::cluster.global.mbarrier::complete_tx::bytes [%0], [%1, {%3, %4}], [%2];" ::"r"(dst), "l"(tm), "r"(bar), "r"(c0), "r"(c1) : "memory");
}
__device__ __forceinline__ void tma3d(uint32_t dst, const CUtensorMap* tm, int c0, int c1, int c2, uint32_t bar) {
  asm volatile("cp.async.bulk.tensor.3d.shared::cluster.global.mbarrier::complete_tx::bytes [%0], [%1, {%3, %4, %5}], [%2];" ::"r"(dst), "l"(tm), "r"(bar), "r"(c0), "r"(c1), "r"(c2) : "memory");
}
__device__ __forceinline__ void bulk1d_store(void* dst, uint32_t src, uint32_t bytes) {
  asm volatile("cp.async.bulk.global.shared::cta.bulk_group [%0], [%1], %2;" ::"l"(dst), "r"(src), "r"(bytes) : "memory");
}
__device__ __forceinline__ void tma2d_store(const CUtensorMap* tm, int c0, int c1, uint32_t src) {
  asm volatile("cp.async.bulk.tensor.2d.global.shared::cta.bulk_group [%0, {%2, %3}], [%1];" ::"l"(tm), "r"(src), "r"(c0), "r"(c1) : "memory");
}
__device__ __forceinline__ void bulk1d(uint32_t dst, const void* src, uint32_t bytes, uint32_t bar) {
  asm volatile("cp.async.bulk.shared::cluster.global.mbarrier::complete_tx::bytes [%0], [%1], %2, [%3];" ::"r"(dst), "l"(src), "r"(bytes), "r"(bar) : "memory");
}
__device__ __forceinline__ void bulk_commit() { asm volatile("cp.async.bulk.commit_group;" ::: "memory"); }
__device__ __forceinline__ void bulk_wait_read0() { asm volatile("cp.async.bulk.wait_group.read 0;" ::: "memory"); }
__device__ __forceinline__ void bulk_wait0() { asm volatile("cp.async.bulk.wait_group 0;" ::: "memory"); }
__device__ __forceinline__ void fence_async_global() { asm volatile("fence.proxy.async.global;" ::: "memory"); }
__device__ __forceinline__ void fence_async_smem() { asm volatile("fence.proxy.async.shared::cta;" ::: "memory"); }
__device__ __forceinline__ void fence_gpu() { asm volatile("fence.acq_rel.gpu;" ::: "memory"); }
__device__ __forceinline__ void nb_sync(int id, int n) { asm volatile("bar.sync %0, %1;" ::"r"(id), "r"(n) : "memory"); }
__device__ __forceinline__ void nb_arrive(int id, int n) { asm volatile("bar.arrive %0, %1;" ::"r"(id), "r"(n) : "memory"); }
__device__ __forceinline__ void wg_fence() { asm volatile("wgmma.fence.sync.aligned;" ::: "memory"); }
__device__ __forceinline__ void wg_commit() { asm volatile("wgmma.commit_group.sync.aligned;" ::: "memory"); }
template <int N> __device__ __forceinline__ void wg_wait() { asm volatile("wgmma.wait_group.sync.aligned %0;" ::"n"(N) : "memory"); }
template <int N> __device__ __forceinline__ void reg_fence(float (&d)[N]) {
#pragma unroll
  for (int i = 0; i < N; i++) asm volatile("" : "+f"(d[i])::"memory");
}
#define FLAG_BACKOFF __nanosleep(20)
__device__ __forceinline__ void flag_add(int idx) { asm volatile("red.release.gpu.global.add.u32 [%0], 1;" ::"l"(&g_flags[idx * 32]) : "memory"); }
__device__ __forceinline__ void flag_add_relaxed(int idx) { asm volatile("red.relaxed.gpu.global.add.u32 [%0], 1;" ::"l"(&g_flags[idx * 32]) : "memory"); }
template <bool ALL>
__device__ __forceinline__ void flag_poll(const unsigned* p, unsigned target) {
  int it = 0;
  while (true) {
    unsigned v;
    asm volatile("ld.relaxed.gpu.global.u32 %0, [%1];" : "=r"(v) : "l"(p) : "memory");
    const bool ok = (int)(v - target) >= 0;
    if (ALL ? (bool)__all_sync(0xffffffffu, ok) : ok) break;
    if (++it > (1 << 21)) __trap();
    FLAG_BACKOFF;
  }
  asm volatile("fence.acquire.gpu;" ::: "memory");
}
__device__ __forceinline__ void flag_wait(int idx, unsigned target) { flag_poll<false>(&g_flags[idx * 32], target); }
__device__ __forceinline__ void flag_wait8(int idx, unsigned target, int lane) { flag_poll<true>(&g_flags[(idx + (lane & 7)) * 32], target); }
__device__ __forceinline__ void flag_wait2(int idx0, unsigned t0, int idx1, unsigned t1, int lane) {
  flag_poll<true>(&g_flags[((lane & 1) ? idx1 : idx0) * 32], (lane & 1) ? t1 : t0);
}
__device__ __forceinline__ uint32_t gtime() { uint32_t t; asm volatile("mov.u32 %0, %%globaltimer_lo;" : "=r"(t)); return t; }
__device__ __forceinline__ void wait_until(uint32_t t) { while ((int)(gtime() - t) < 0) {} }
__device__ __forceinline__ void tgate_arrive(int gate, int gpc, unsigned ep, uint32_t delay) {
  if (((atomicAdd(&g_flags[(FL_TG + gate * 8 + gpc) * 32], 1u) + 1) & 15) == 0)
    asm volatile("st.relaxed.gpu.global.u64 [%0], %1;" ::"l"(&g_t0[(gate * 8 + gpc) * 16]), "l"(((unsigned long long)ep << 32) | (gtime() + delay)) : "memory");
}
__device__ __forceinline__ uint32_t tgate_poll(int gate, int gpc, unsigned ep) {
  unsigned long long v;
  int it = 0;
  do {
    asm volatile("ld.relaxed.gpu.global.u64 %0, [%1];" : "=l"(v) : "l"(&g_t0[(gate * 8 + gpc) * 16]) : "memory");
    if (++it > (1 << 21)) __trap();
  } while ((unsigned)(v >> 32) != ep);
  return (uint32_t)v;
}
__device__ __forceinline__ unsigned ld_epoch() {
  unsigned v;
  asm volatile("ld.relaxed.gpu.global.u32 %0, [%1];" : "=r"(v) : "l"(&g_epoch[0]) : "memory");
  return v;
}
template <uint32_t OFF, uint32_t LBO, uint32_t SBO, uint32_t SWZ>
__device__ __forceinline__ uint64_t mkdesc(uint32_t a16) {
  const uint32_t lo = a16 + ((OFF >> 4) | ((LBO >> 4) << 16));
  constexpr uint32_t hi = (SBO >> 4) | (SWZ << 30);
  return ((uint64_t)hi << 32) | lo;
}
template <uint32_t OFF, uint32_t LBO = 16> __device__ __forceinline__ uint64_t desc_sw128(uint32_t a16) { return mkdesc<OFF, LBO, 1024, 1>(a16); }
template <uint32_t OFF, uint32_t LBO, uint32_t SBO> __device__ __forceinline__ uint64_t desc_nosw(uint32_t a16) { return mkdesc<OFF, LBO, SBO, 0>(a16); }
template <int I, int N, class F> __device__ __forceinline__ void static_for(F&& f) {
  if constexpr (I < N) { f(std::integral_constant<int, I>{}); static_for<I + 1, N>(f); }
}
__device__ __forceinline__ float ex2(float x) { float y; asm("ex2.approx.ftz.f32 %0, %1;" : "=f"(y) : "f"(x)); return y; }
__device__ __forceinline__ float rcp(float x) { float y; asm("rcp.approx.ftz.f32 %0, %1;" : "=f"(y) : "f"(x)); return y; }
__device__ __forceinline__ float sqrt_fast(float x) { float y; asm("sqrt.approx.ftz.f32 %0, %1;" : "=f"(y) : "f"(x)); return y; }
__device__ __forceinline__ float tanh_fast(float x) { float y; asm("tanh.approx.f32 %0, %1;" : "=f"(y) : "f"(x)); return y; }
__device__ __forceinline__ float silu_half(float h) { return fmaf(h, tanh_fast(h), h); }
__device__ __forceinline__ uint32_t pack2(float lo, float hi) { uint32_t r; asm("cvt.rn.bf16x2.f32 %0, %1, %2;" : "=r"(r) : "f"(hi), "f"(lo)); return r; }
__device__ __forceinline__ float bf_lo(uint32_t v) { return __uint_as_float(v << 16); }
__device__ __forceinline__ float bf_hi(uint32_t v) { return __uint_as_float(v & 0xFFFF0000u); }
__device__ __forceinline__ float bf_round(float x) { return __bfloat162float(__float2bfloat16_rn(x)); }
__device__ __forceinline__ uint32_t ldg32(const void* p) { uint32_t v; asm volatile("ld.global.nc.u32 %0, [%1];" : "=r"(v) : "l"(p)); return v; }
__device__ __forceinline__ uint32_t ldg16(const void* p) { unsigned short v; asm volatile("ld.global.nc.u16 %0, [%1];" : "=h"(v) : "l"(p)); return v; }
__device__ __forceinline__ uint4 ldg128(const void* p) { uint4 v; asm volatile("ld.global.nc.v4.u32 {%0,%1,%2,%3}, [%4];" : "=r"(v.x), "=r"(v.y), "=r"(v.z), "=r"(v.w) : "l"(p)); return v; }
__device__ __forceinline__ float ldcg_f(const float* p) { float v; asm volatile("ld.relaxed.gpu.global.f32 %0, [%1];" : "=f"(v) : "l"(p) : "memory"); return v; }
__device__ __forceinline__ float2 ldcg_f2(const float2* p) { float2 v; asm volatile("ld.relaxed.gpu.global.v2.f32 {%0,%1}, [%2];" : "=f"(v.x), "=f"(v.y) : "l"(p) : "memory"); return v; }
__device__ __forceinline__ float4 ldcg_f4(const float* p) { float4 v; asm volatile("ld.relaxed.gpu.global.v4.f32 {%0,%1,%2,%3}, [%4];" : "=f"(v.x), "=f"(v.y), "=f"(v.z), "=f"(v.w) : "l"(p) : "memory"); return v; }
__device__ __forceinline__ uint32_t lds32(uint32_t a) { uint32_t v; asm volatile("ld.shared.u32 %0, [%1];" : "=r"(v) : "r"(a) : "memory"); return v; }
__device__ __forceinline__ uint32_t lds16(uint32_t a) { unsigned short v; asm volatile("ld.shared.u16 %0, [%1];" : "=h"(v) : "r"(a) : "memory"); return v; }
__device__ __forceinline__ void sts32(uint32_t a, uint32_t x) { asm volatile("st.shared.u32 [%0], %1;" ::"r"(a), "r"(x) : "memory"); }
__device__ __forceinline__ void sts128(uint32_t a, uint32_t x, uint32_t y, uint32_t z, uint32_t w) { asm volatile("st.shared.v4.u32 [%0], {%1,%2,%3,%4};" ::"r"(a), "r"(x), "r"(y), "r"(z), "r"(w) : "memory"); }
__device__ __forceinline__ void sts64(uint32_t a, uint32_t x, uint32_t y) { asm volatile("st.shared.v2.u32 [%0], {%1,%2};" ::"r"(a), "r"(x), "r"(y) : "memory"); }
__device__ __forceinline__ uint4 lds128(uint32_t a) { uint4 v; asm volatile("ld.shared.v4.u32 {%0,%1,%2,%3}, [%4];" : "=r"(v.x), "=r"(v.y), "=r"(v.z), "=r"(v.w) : "r"(a) : "memory"); return v; }
__device__ __forceinline__ uint2 lds64(uint32_t a) { uint2 v; asm volatile("ld.shared.v2.u32 {%0,%1}, [%2];" : "=r"(v.x), "=r"(v.y) : "r"(a) : "memory"); return v; }
__device__ __forceinline__ float2 lds_f2(uint32_t a) { float2 v; asm volatile("ld.shared.v2.f32 {%0,%1}, [%2];" : "=f"(v.x), "=f"(v.y) : "r"(a) : "memory"); return v; }
__device__ __forceinline__ void red_f32(float* p, float v) { asm volatile("red.relaxed.gpu.global.add.f32 [%0], %1;" ::"l"(p), "f"(v) : "memory"); }
__device__ __forceinline__ void red_f32x2(float* p, float a, float b) { asm volatile("red.relaxed.gpu.global.add.v2.f32 [%0], {%1, %2};" ::"l"(p), "f"(a), "f"(b) : "memory"); }
__device__ __forceinline__ void mma16816_z(float (&c)[4], uint32_t a0, uint32_t a1, uint32_t a2, uint32_t a3, uint32_t b0, uint32_t b1) {
  asm volatile("mma.sync.aligned.m16n8k16.row.col.f32.bf16.bf16.f32 {%0,%1,%2,%3}, {%4,%5,%6,%7}, {%8,%9}, {%10,%10,%10,%10};"
               : "=f"(c[0]), "=f"(c[1]), "=f"(c[2]), "=f"(c[3])
               : "r"(a0), "r"(a1), "r"(a2), "r"(a3), "r"(b0), "r"(b1), "f"(0.f));
}
__device__ __forceinline__ void mma16816(float (&c)[4], uint32_t a0, uint32_t a1, uint32_t a2, uint32_t a3, uint32_t b0, uint32_t b1) {
  asm volatile("mma.sync.aligned.m16n8k16.row.col.f32.bf16.bf16.f32 {%0,%1,%2,%3}, {%4,%5,%6,%7}, {%8,%9}, {%0,%1,%2,%3};"
               : "+f"(c[0]), "+f"(c[1]), "+f"(c[2]), "+f"(c[3])
               : "r"(a0), "r"(a1), "r"(a2), "r"(a3), "r"(b0), "r"(b1));
}

__device__ __forceinline__ void wg_n128_tb(float (&d)[64], uint64_t da, uint64_t db, int sd) {
  asm volatile("{\n.reg .pred p;\nsetp.ne.b32 p, %66, 0;\n"
    "wgmma.mma_async.sync.aligned.m64n128k16.f32.bf16.bf16 {%0, %1, %2, %3, %4, %5, %6, %7, %8, %9, %10, %11, %12, %13, %14, %15, %16, %17, %18, %19, %20, %21, %22, %23, %24, %25, %26, %27, %28, %29, %30, %31, %32, %33, %34, %35, %36, %37, %38, %39, %40, %41, %42, %43, %44, %45, %46, %47, %48, %49, %50, %51, %52, %53, %54, %55, %56, %57, %58, %59, %60, %61, %62, %63}, %64, %65, p, 1, 1, 0, 1;\n}\n"
    : "+f"(d[0]), "+f"(d[1]), "+f"(d[2]), "+f"(d[3]), "+f"(d[4]), "+f"(d[5]), "+f"(d[6]), "+f"(d[7]), "+f"(d[8]), "+f"(d[9]), "+f"(d[10]), "+f"(d[11]), "+f"(d[12]), "+f"(d[13]), "+f"(d[14]), "+f"(d[15]), "+f"(d[16]), "+f"(d[17]), "+f"(d[18]), "+f"(d[19]), "+f"(d[20]), "+f"(d[21]), "+f"(d[22]), "+f"(d[23]), "+f"(d[24]), "+f"(d[25]), "+f"(d[26]), "+f"(d[27]), "+f"(d[28]), "+f"(d[29]), "+f"(d[30]), "+f"(d[31]), "+f"(d[32]), "+f"(d[33]), "+f"(d[34]), "+f"(d[35]), "+f"(d[36]), "+f"(d[37]), "+f"(d[38]), "+f"(d[39]), "+f"(d[40]), "+f"(d[41]), "+f"(d[42]), "+f"(d[43]), "+f"(d[44]), "+f"(d[45]), "+f"(d[46]), "+f"(d[47]), "+f"(d[48]), "+f"(d[49]), "+f"(d[50]), "+f"(d[51]), "+f"(d[52]), "+f"(d[53]), "+f"(d[54]), "+f"(d[55]), "+f"(d[56]), "+f"(d[57]), "+f"(d[58]), "+f"(d[59]), "+f"(d[60]), "+f"(d[61]), "+f"(d[62]), "+f"(d[63])
    : "l"(da), "l"(db), "r"(sd));
}
__device__ __forceinline__ void wg_n144(float (&d)[72], uint64_t da, uint64_t db, int sd) {
  asm volatile("{\n.reg .pred p;\nsetp.ne.b32 p, %74, 0;\n"
    "wgmma.mma_async.sync.aligned.m64n144k16.f32.bf16.bf16 {%0, %1, %2, %3, %4, %5, %6, %7, %8, %9, %10, %11, %12, %13, %14, %15, %16, %17, %18, %19, %20, %21, %22, %23, %24, %25, %26, %27, %28, %29, %30, %31, %32, %33, %34, %35, %36, %37, %38, %39, %40, %41, %42, %43, %44, %45, %46, %47, %48, %49, %50, %51, %52, %53, %54, %55, %56, %57, %58, %59, %60, %61, %62, %63, %64, %65, %66, %67, %68, %69, %70, %71}, %72, %73, p, 1, 1, 0, 0;\n}\n"
    : "+f"(d[0]), "+f"(d[1]), "+f"(d[2]), "+f"(d[3]), "+f"(d[4]), "+f"(d[5]), "+f"(d[6]), "+f"(d[7]), "+f"(d[8]), "+f"(d[9]), "+f"(d[10]), "+f"(d[11]), "+f"(d[12]), "+f"(d[13]), "+f"(d[14]), "+f"(d[15]), "+f"(d[16]), "+f"(d[17]), "+f"(d[18]), "+f"(d[19]), "+f"(d[20]), "+f"(d[21]), "+f"(d[22]), "+f"(d[23]), "+f"(d[24]), "+f"(d[25]), "+f"(d[26]), "+f"(d[27]), "+f"(d[28]), "+f"(d[29]), "+f"(d[30]), "+f"(d[31]), "+f"(d[32]), "+f"(d[33]), "+f"(d[34]), "+f"(d[35]), "+f"(d[36]), "+f"(d[37]), "+f"(d[38]), "+f"(d[39]), "+f"(d[40]), "+f"(d[41]), "+f"(d[42]), "+f"(d[43]), "+f"(d[44]), "+f"(d[45]), "+f"(d[46]), "+f"(d[47]), "+f"(d[48]), "+f"(d[49]), "+f"(d[50]), "+f"(d[51]), "+f"(d[52]), "+f"(d[53]), "+f"(d[54]), "+f"(d[55]), "+f"(d[56]), "+f"(d[57]), "+f"(d[58]), "+f"(d[59]), "+f"(d[60]), "+f"(d[61]), "+f"(d[62]), "+f"(d[63]), "+f"(d[64]), "+f"(d[65]), "+f"(d[66]), "+f"(d[67]), "+f"(d[68]), "+f"(d[69]), "+f"(d[70]), "+f"(d[71])
    : "l"(da), "l"(db), "r"(sd));
}
__device__ __forceinline__ void wg_n160(float (&d)[80], uint64_t da, uint64_t db, int sd) {
  asm volatile("{\n.reg .pred p;\nsetp.ne.b32 p, %82, 0;\n"
    "wgmma.mma_async.sync.aligned.m64n160k16.f32.bf16.bf16 {%0, %1, %2, %3, %4, %5, %6, %7, %8, %9, %10, %11, %12, %13, %14, %15, %16, %17, %18, %19, %20, %21, %22, %23, %24, %25, %26, %27, %28, %29, %30, %31, %32, %33, %34, %35, %36, %37, %38, %39, %40, %41, %42, %43, %44, %45, %46, %47, %48, %49, %50, %51, %52, %53, %54, %55, %56, %57, %58, %59, %60, %61, %62, %63, %64, %65, %66, %67, %68, %69, %70, %71, %72, %73, %74, %75, %76, %77, %78, %79}, %80, %81, p, 1, 1, 0, 0;\n}\n"
    : "+f"(d[0]), "+f"(d[1]), "+f"(d[2]), "+f"(d[3]), "+f"(d[4]), "+f"(d[5]), "+f"(d[6]), "+f"(d[7]), "+f"(d[8]), "+f"(d[9]), "+f"(d[10]), "+f"(d[11]), "+f"(d[12]), "+f"(d[13]), "+f"(d[14]), "+f"(d[15]), "+f"(d[16]), "+f"(d[17]), "+f"(d[18]), "+f"(d[19]), "+f"(d[20]), "+f"(d[21]), "+f"(d[22]), "+f"(d[23]), "+f"(d[24]), "+f"(d[25]), "+f"(d[26]), "+f"(d[27]), "+f"(d[28]), "+f"(d[29]), "+f"(d[30]), "+f"(d[31]), "+f"(d[32]), "+f"(d[33]), "+f"(d[34]), "+f"(d[35]), "+f"(d[36]), "+f"(d[37]), "+f"(d[38]), "+f"(d[39]), "+f"(d[40]), "+f"(d[41]), "+f"(d[42]), "+f"(d[43]), "+f"(d[44]), "+f"(d[45]), "+f"(d[46]), "+f"(d[47]), "+f"(d[48]), "+f"(d[49]), "+f"(d[50]), "+f"(d[51]), "+f"(d[52]), "+f"(d[53]), "+f"(d[54]), "+f"(d[55]), "+f"(d[56]), "+f"(d[57]), "+f"(d[58]), "+f"(d[59]), "+f"(d[60]), "+f"(d[61]), "+f"(d[62]), "+f"(d[63]), "+f"(d[64]), "+f"(d[65]), "+f"(d[66]), "+f"(d[67]), "+f"(d[68]), "+f"(d[69]), "+f"(d[70]), "+f"(d[71]), "+f"(d[72]), "+f"(d[73]), "+f"(d[74]), "+f"(d[75]), "+f"(d[76]), "+f"(d[77]), "+f"(d[78]), "+f"(d[79])
    : "l"(da), "l"(db), "r"(sd));
}
__device__ __forceinline__ void wg_n80(float (&d)[40], uint64_t da, uint64_t db, int sd) {
  asm volatile("{\n.reg .pred p;\nsetp.ne.b32 p, %42, 0;\n"
    "wgmma.mma_async.sync.aligned.m64n80k16.f32.bf16.bf16 {%0, %1, %2, %3, %4, %5, %6, %7, %8, %9, %10, %11, %12, %13, %14, %15, %16, %17, %18, %19, %20, %21, %22, %23, %24, %25, %26, %27, %28, %29, %30, %31, %32, %33, %34, %35, %36, %37, %38, %39}, %40, %41, p, 1, 1, 0, 0;\n}\n"
    : "+f"(d[0]), "+f"(d[1]), "+f"(d[2]), "+f"(d[3]), "+f"(d[4]), "+f"(d[5]), "+f"(d[6]), "+f"(d[7]), "+f"(d[8]), "+f"(d[9]), "+f"(d[10]), "+f"(d[11]), "+f"(d[12]), "+f"(d[13]), "+f"(d[14]), "+f"(d[15]), "+f"(d[16]), "+f"(d[17]), "+f"(d[18]), "+f"(d[19]), "+f"(d[20]), "+f"(d[21]), "+f"(d[22]), "+f"(d[23]), "+f"(d[24]), "+f"(d[25]), "+f"(d[26]), "+f"(d[27]), "+f"(d[28]), "+f"(d[29]), "+f"(d[30]), "+f"(d[31]), "+f"(d[32]), "+f"(d[33]), "+f"(d[34]), "+f"(d[35]), "+f"(d[36]), "+f"(d[37]), "+f"(d[38]), "+f"(d[39])
    : "l"(da), "l"(db), "r"(sd));
}
__device__ __forceinline__ void wg_n24_tatb(float (&d)[12], uint64_t da, uint64_t db, int sd) {
  asm volatile("{\n.reg .pred p;\nsetp.ne.b32 p, %14, 0;\n"
    "wgmma.mma_async.sync.aligned.m64n24k16.f32.bf16.bf16 {%0, %1, %2, %3, %4, %5, %6, %7, %8, %9, %10, %11}, %12, %13, p, 1, 1, 1, 1;\n}\n"
    : "+f"(d[0]), "+f"(d[1]), "+f"(d[2]), "+f"(d[3]), "+f"(d[4]), "+f"(d[5]), "+f"(d[6]), "+f"(d[7]), "+f"(d[8]), "+f"(d[9]), "+f"(d[10]), "+f"(d[11])
    : "l"(da), "l"(db), "r"(sd));
}
__device__ __forceinline__ void wg_n88_rs(float (&d)[44], uint32_t a0, uint32_t a1, uint32_t a2, uint32_t a3, uint64_t db, int sd) {
  asm volatile("{\n.reg .pred p;\nsetp.ne.b32 p, %49, 0;\n"
    "wgmma.mma_async.sync.aligned.m64n88k16.f32.bf16.bf16 {%0, %1, %2, %3, %4, %5, %6, %7, %8, %9, %10, %11, %12, %13, %14, %15, %16, %17, %18, %19, %20, %21, %22, %23, %24, %25, %26, %27, %28, %29, %30, %31, %32, %33, %34, %35, %36, %37, %38, %39, %40, %41, %42, %43}, {%44, %45, %46, %47}, %48, p, 1, 1, 0;\n}\n"
    : "+f"(d[0]), "+f"(d[1]), "+f"(d[2]), "+f"(d[3]), "+f"(d[4]), "+f"(d[5]), "+f"(d[6]), "+f"(d[7]), "+f"(d[8]), "+f"(d[9]), "+f"(d[10]), "+f"(d[11]), "+f"(d[12]), "+f"(d[13]), "+f"(d[14]), "+f"(d[15]), "+f"(d[16]), "+f"(d[17]), "+f"(d[18]), "+f"(d[19]), "+f"(d[20]), "+f"(d[21]), "+f"(d[22]), "+f"(d[23]), "+f"(d[24]), "+f"(d[25]), "+f"(d[26]), "+f"(d[27]), "+f"(d[28]), "+f"(d[29]), "+f"(d[30]), "+f"(d[31]), "+f"(d[32]), "+f"(d[33]), "+f"(d[34]), "+f"(d[35]), "+f"(d[36]), "+f"(d[37]), "+f"(d[38]), "+f"(d[39]), "+f"(d[40]), "+f"(d[41]), "+f"(d[42]), "+f"(d[43])
    : "r"(a0), "r"(a1), "r"(a2), "r"(a3), "l"(db), "r"(sd));
}

struct NoHook { __device__ __forceinline__ void operator()(int) const {} };
template <int NKB, bool RING2 = false, class Issue, class Hook = NoHook>
__device__ __forceinline__ void mainloop(int idx0, int lane, int order_bar, Issue&& issue, Hook&& hook = Hook()) {
  constexpr int NS = RING2 ? NSLOT2 : NSLOT, SB = RING2 ? SLOT2_BYTES : SLOT_BYTES;
  constexpr uint32_t bfull = SBASE + OFF_BAR + (RING2 ? B_FULL2 : B_FULL), bempty = SBASE + OFF_BAR + (RING2 ? B_EMPTY2 : B_EMPTY);
  constexpr int TLO = RING2 ? 30 : 0;
  (void)TLO;
  int slot = idx0 % NS;
  uint32_t ph = (idx0 / NS) & 1;
  int prev = slot;
  bool ready = false;
#pragma unroll 1
  for (int kb = 0; kb < NKB; kb++) {
    if (!ready) mbar_wait(bfull + slot * 8, ph);
    wg_fence();
    issue((SBASE >> 4) + slot * (SB >> 4), kb);
    wg_commit();
    if (kb == NKB - 1 && order_bar >= 0) nb_arrive(order_bar, 256);
    hook(kb);
    const int cur = slot;
    if (++slot == NS) { slot = 0; ph ^= 1; }
    ready = EARLY_TEST && kb + 1 < NKB && mbar_test(bfull + slot * 8, ph);
    wg_wait<1>();
    if (kb > 0 && lane == 0) mbar_arrive(bempty + prev * 8);
    prev = cur;
  }
  wg_wait<0>();
  if (lane == 0) mbar_arrive(bempty + prev * 8);
}

template <int NG, int OFF, int N>
__device__ __forceinline__ void epi_h(const float (&a0)[N], const float2 (&cs)[NG], float2 r0, float2 r1, __nv_bfloat16* hp) {
  const float h0 = 0.5f * r0.x, h1 = 0.5f * r1.x;
#pragma unroll
  for (int q = 0; q < NG / 4; q++) {
    uint32_t w0[4], w1[4];
#pragma unroll
    for (int t = 0; t < 4; t++) {
      const int g = 4 * q + t;
      w0[t] = pack2(silu_half(h0 * fmaf(r0.y, cs[g].x, a0[OFF + 4 * g + 0])), silu_half(h0 * fmaf(r0.y, cs[g].y, a0[OFF + 4 * g + 1])));
      w1[t] = pack2(silu_half(h1 * fmaf(r1.y, cs[g].x, a0[OFF + 4 * g + 2])), silu_half(h1 * fmaf(r1.y, cs[g].y, a0[OFF + 4 * g + 3])));
    }
    *reinterpret_cast<uint4*>(hp + 32 * q) = make_uint4(w0[0], w0[1], w0[2], w0[3]);
    *reinterpret_cast<uint4*>(hp + 8 * FF + 32 * q) = make_uint4(w1[0], w1[1], w1[2], w1[3]);
  }
}

__device__ __forceinline__ float ex2_fma(float x) {
  x = fmaxf(x, -126.0f);
  const float t = x + 12582912.0f;
  const float f = x - (t - 12582912.0f);
  float p = fmaf(0.009570101276040077f, f, 0.05591785907745361f);
  p = fmaf(p, f, 0.240247443318367f);
  p = fmaf(p, f, 0.6931217908859253f);
  p = fmaf(p, f, 0.9999992847442627f);
  return __int_as_float(__float_as_int(p) + (__float_as_int(t) << 23));
}
__device__ __forceinline__ void softmax_exp(const float (&p)[20], float a2, float (&e)[40]) {
  float mx[4], mn[4];
#pragma unroll
  for (int q = 0; q < 4; q++) {
    mx[q] = fmaxf(fmaxf(p[5 * q], p[5 * q + 1]), fmaxf(p[5 * q + 2], fmaxf(p[5 * q + 3], p[5 * q + 4])));
    mn[q] = fminf(fminf(p[5 * q], p[5 * q + 1]), fminf(p[5 * q + 2], fminf(p[5 * q + 3], p[5 * q + 4])));
  }
  const float mxs = -a2 * fmaxf(fmaxf(mx[0], mx[1]), fmaxf(mx[2], mx[3])), mns = a2 * fminf(fminf(mn[0], mn[1]), fminf(mn[2], mn[3]));
#pragma unroll
  for (int f = 0; f < 20; f++) {
    e[f] = ex2(fmaf(a2, p[f], mxs));
    e[20 + f] = ex2(fmaf(-a2, p[f], mns));
  }
}
__device__ __forceinline__ bool split_block() { uint32_t v; asm volatile("mov.u32 %0, %%nwarpid;" : "=r"(v)); return v != 0; }
__device__ __forceinline__ void softmax_norm(const float (&e)[40], uint32_t (&w)[20]) {
  float s[8];
#pragma unroll
  for (int q = 0; q < 8; q++) s[q] = ((e[5 * q] + e[5 * q + 1]) + (e[5 * q + 2] + e[5 * q + 3])) + e[5 * q + 4];
  const float rp = rcp((s[0] + s[1]) + (s[2] + s[3])), rn = rcp((s[4] + s[5]) + (s[6] + s[7]));
#pragma unroll
  for (int t = 0; t < 10; t++) {
    w[t] = pack2(e[2 * t] * rp, e[2 * t + 1] * rp);
    w[10 + t] = pack2(e[20 + 2 * t] * rn, e[20 + 2 * t + 1] * rn);
  }
}

__device__ __forceinline__ void transpose_item(const __nv_bfloat16* src, int st2, int st1, uint8_t* dst) {
  uint32_t v[8];
#pragma unroll
  for (int m = 0; m < 4; m++) { v[2 * m] = ldg32(src + m * st2); v[2 * m + 1] = ldg32(src + m * st2 + st1); }
  *reinterpret_cast<uint4*>(dst) =
      make_uint4(__byte_perm(v[0], v[1], 0x5410), __byte_perm(v[2], v[3], 0x5410), __byte_perm(v[4], v[5], 0x5410), __byte_perm(v[6], v[7], 0x5410));
  *reinterpret_cast<uint4*>(dst + 16) =
      make_uint4(__byte_perm(v[0], v[1], 0x7632), __byte_perm(v[2], v[3], 0x7632), __byte_perm(v[4], v[5], 0x7632), __byte_perm(v[6], v[7], 0x7632));
}

__global__ void __launch_bounds__(384, 1) fused_kernel(const __grid_constant__ Params P) {
  extern __shared__ __align__(1024) uint8_t smem_raw[];
  constexpr uint32_t sbase = SBASE;
  constexpr uint32_t bar = sbase + OFF_BAR;
  constexpr uint32_t stg = sbase + OFF_STG;
  const int tid = threadIdx.x, warp = __shfl_sync(0xffffffffu, tid >> 5, 0), lane = tid & 31;
  const int bid = blockIdx.x;
  const bool helper = (bid >= 112 && bid < 114) || bid >= 130;
  const int work = bid < 112 ? bid : bid - 2;
  const int r = work >> 3, c = work & 7;
  const int li = lane >> 2, lj = lane & 3;

  if (helper) {
    constexpr int NIN = 8, NOUT = 3;
    constexpr uint32_t IN0 = SBASE, OUT0 = SBASE + NIN * 20480, HB = OUT0 + NOUT * 20480;
    constexpr uint32_t H_FULL = HB, H_EMPTY = HB + 64, H_ORDY = HB + 128, H_OFREE = HB + 192;
    const int hs = bid < 114 ? bid - 112 : bid - 128;
    if (tid == 0) {
      TL(1);
      if (smem_u32(smem_raw) != sbase) __trap();
      for (int q = 0; q < NIN; q++) { mbar_init(H_FULL + q * 8, 1); mbar_init(H_EMPTY + q * 8, 10); }
      for (int q = 0; q < NOUT; q++) { mbar_init(H_ORDY + q * 8, 10); mbar_init(H_OFREE + q * 8, 1); }
      asm volatile("fence.mbarrier_init.release.cluster;" ::: "memory");
    }
    __syncthreads();
    if (warp == 10) {
      if (lane == 0) {
#pragma unroll 1
        for (int kbg = 0; kbg < 34; kbg++) {
          const int q = kbg % NIN;
          mbar_wait_trap(H_EMPTY + q * 8, ((kbg / NIN) & 1) ^ 1);
          mbar_expect_tx(H_FULL + q * 8, 20480);
          const bool isw2 = kbg < 24;
          const int row = isw2 ? (kbg < 16 ? 192 * (kbg >> 1) + 64 * (kbg & 1) : 192 * (kbg - 16) + 128) : 64 * (kbg - 24);
          tma2d(IN0 + q * 20480, isw2 ? &P.tm_w2 : &P.tm_wo, 160 * hs, row, H_FULL + q * 8);
        }
      }
    } else if (warp == 11) {
      if (lane == 0) {
#pragma unroll 1
        for (int kbg = 0; kbg < 34; kbg++) {
          const int q = kbg % NOUT;
          mbar_wait_trap(H_ORDY + q * 8, (kbg / NOUT) & 1);
          bulk1d_store(g_wp3 + (hs * 34 + kbg) * 20480, OUT0 + q * 20480, 20480);
          bulk_commit();
          if (kbg > 0) {
            asm volatile("cp.async.bulk.wait_group.read 1;" ::: "memory");
            mbar_arrive(H_OFREE + ((kbg - 1) % NOUT) * 8);
          }
          if (kbg == 16 || kbg == 24) {
            asm volatile("cp.async.bulk.wait_group 1;" ::: "memory");
            flag_add_relaxed(FL_P3W + 2 * hs);
            flag_add_relaxed(FL_P3W + 2 * hs + 1);
            TL(41);
          }
        }
        bulk_wait0();
        flag_add_relaxed(FL_P3W + 2 * hs);
        flag_add_relaxed(FL_P3W + 2 * hs + 1);
        TL(42);
      }
    } else {
      const int kc = tid / 40, rem = tid - kc * 40, j = rem & 3, g = rem >> 2;
      const uint32_t so_w2 = (32 * (kc >> 2) + 2 * (kc & 3)) * 320 + (20 * j + g) * 4;
      const uint32_t so_wo = (8 * kc) * 320 + (20 * j + g) * 4;
      const uint32_t dof = kc * 2560 + (8 * g + 2 * j) * 16;
      const bool odd = g & 1;
      const uint32_t sel0 = odd ? 0x7632u : 0x5410u, sel1 = odd ? 0x5410u : 0x7632u, o0 = odd ? 16u : 0u;
#pragma unroll 1
      for (int kbg = 0; kbg < 34; kbg++) {
        const int qi = kbg % NIN, qo = kbg % NOUT;
        const bool isw2 = kbg < 24;
        const uint32_t a = IN0 + qi * 20480 + (isw2 ? so_w2 : so_wo), st2 = isw2 ? 8 * 320 : 2 * 320;
        mbar_wait_trap(H_FULL + qi * 8, (kbg / NIN) & 1);
        uint32_t v[2][8];
#pragma unroll
        for (int t = 0; t < 2; t++)
#pragma unroll
          for (int m = 0; m < 4; m++) { v[t][2 * m] = lds32(a + t * 40 + m * st2); v[t][2 * m + 1] = lds32(a + t * 40 + m * st2 + 320); }
        mbar_wait_trap(H_OFREE + qo * 8, ((kbg / NOUT) & 1) ^ 1);
#pragma unroll
        for (int t = 0; t < 2; t++) {
          const uint32_t (&u)[8] = v[t];
          const uint32_t out = OUT0 + qo * 20480 + t * 1280 + dof;
          sts128(out + o0, __byte_perm(u[0], u[1], sel0), __byte_perm(u[2], u[3], sel0), __byte_perm(u[4], u[5], sel0), __byte_perm(u[6], u[7], sel0));
          sts128(out + 16 - o0, __byte_perm(u[0], u[1], sel1), __byte_perm(u[2], u[3], sel1), __byte_perm(u[4], u[5], sel1), __byte_perm(u[6], u[7], sel1));
        }
        fence_async_smem();
        __syncwarp();
        if (lane == 0) { mbar_arrive(H_EMPTY + qi * 8); mbar_arrive(H_ORDY + qo * 8); }
      }
    }
    return;
  }

  if (tid == 0) {
    TLG(0); TL(1);
    if (smem_u32(smem_raw) != sbase) __trap();
#pragma unroll
    for (int s = 0; s < NSLOT; s++) { mbar_init(bar + B_FULL + s * 8, 1); mbar_init(bar + B_EMPTY + s * 8, 4); }
    mbar_init(bar + B_CONST, 1);
    mbar_init(bar + B_XF, 1);
    mbar_init(bar + B_PIN, 1);
    mbar_init(bar + B_SDONE, 8);
    mbar_init(bar + B_KVP, 4);
    mbar_init(bar + B_KVS, 8);
    mbar_init(bar + B_QS, 5);
    mbar_init(bar + B_GATE3, 1);
    mbar_init(bar + B_GATE4, 1);
    mbar_init(bar + B_HAP, 4);
    mbar_init(bar + B_HBP, 4);
    mbar_init(bar + B_KVOK, 1);
    mbar_init(bar + B_GATE1, 1);
    mbar_init(bar + B_GATE2, 1);
    mbar_init(bar + B_GO6W, 1);
    mbar_init(bar + B_T1E, 4);
    mbar_init(bar + B_E2E, 4);
#pragma unroll
    for (int q = 0; q < NSLOT2; q++) { mbar_init(bar + B_FULL2 + q * 8, 1); mbar_init(bar + B_EMPTY2 + q * 8, 4); }
#pragma unroll
    for (int q = 0; q < 5; q++) mbar_init(bar + B_GO2 + q * 8, 1);
    asm volatile("fence.mbarrier_init.release.cluster;" ::: "memory");
    TL(10);
    mbar_expect_tx(bar + B_PIN, 3 * 6400 + 3200);
    tma2d(stg + WIN_OFF + 6400, &P.tm_wqkv, 640 + 80 * c, 40 * r, bar + B_PIN);
    tma2d(stg + WIN_OFF + 12800, &P.tm_wqkv, 1280 + 80 * c, 40 * r, bar + B_PIN);
    bulk1d(sbase + OFF_PHI, P.wphi + c * 1600, 3200, bar + B_PIN);
    tma2d(stg + WIN_OFF, &P.tm_wqkv, 80 * c, 40 * r, bar + B_PIN);
#pragma unroll 1
    for (int k = 0; k < 2; k++) {
      mbar_expect_tx(bar + B_FULL + k * 8, 32768);
      tma2d(sbase + k * SLOT_BYTES, &P.tm_x, k * 64, r * 128, bar + B_FULL + k * 8);
      tma3d(sbase + k * SLOT_BYTES + 16384, &P.tm_w1b, 0, k * 64, 3 * c, bar + B_FULL + k * 8);
    }
    asm volatile("cp.async.bulk.prefetch.L2.global [%0], %1;" ::"l"(P.x + (size_t)work * 16 * DM), "r"(20480) : "memory");
    asm volatile("cp.async.bulk.prefetch.L2.global [%0], %1;" ::"l"(P.w1 + (size_t)work * 5 * FF), "r"(15360) : "memory");
    TL(11);
  }
  __syncthreads();

  if (warp < 4) {
    asm volatile("setmaxnreg.dec.sync.aligned.u32 40;");
    if (warp == 0) {
      if (lane == 0) {
        uint32_t s = sbase + 2 * SLOT_BYTES, fb = bar + B_FULL + 16, ph = 1;
        auto acquire = [&](uint32_t bytes, uint32_t period) {
          mbar_wait_trap(fb + (B_EMPTY - B_FULL), ph);
          mbar_expect_tx(fb, bytes);
        };
        auto advance = [&]() {
          s += SLOT_BYTES; fb += 8;
          if (fb == bar + B_FULL + NSLOT * 8) { s = sbase; fb = bar + B_FULL; ph ^= 1; }
        };
        const int row = r * 128;
#pragma unroll 1
        for (int k = 128; k < 640; k += 64) {
          acquire(32768, 0);
          tma2d(s, &P.tm_x, k, row, fb);
          tma3d(s + 16384, &P.tm_w1b, 0, k, 3 * c, fb);
          PTL(192 + k / 64);
          advance();
        }
        TL(2); mbar_wait_trap(bar + B_GO2, 0); fence_async_global(); TL(3);
        {
          const uint8_t* src = g_wkv + c * 204800;
#pragma unroll 1
          for (int k = 0; k < 640; k += 64, src += 20480) {
            acquire(36864, PACE2);
            tma2d(s, &P.tm_x, k, row, fb);
            bulk1d(s + 16384, src, 20480, fb);
            PTL(202 + k / 64);
            advance();
          }
        }
        mbar_wait_trap(bar + B_GO3, 0); fence_async_global();
        {
          const uint8_t* src = g_wqh + c * 184320;
#pragma unroll 1
          for (int k = 0; k < 640; k += 64, src += 18432) {
            acquire(34816, PACE3);
            tma2d(s, &P.tm_x, k, row, fb);
            bulk1d(s + 16384, src, 18432, fb);
            PTL(212 + k / 64);
            advance();
          }
        }
        TL(4); mbar_wait_trap(bar + B_GO4, 0); fence_async_global(); TL(5);
        const int row3 = row + 64 * (c & 1);
        uint32_t s2 = sbase, f2 = bar + B_FULL2, e2 = bar + B_EMPTY, p2 = 1;
        auto step = [&](const CUtensorMap* tm, int k) {
          mbar_wait_trap(e2, p2);
          mbar_expect_tx(f2, 28672);
          tma2d(s2, tm, k, row3, f2);
          s2 += SLOT2_BYTES; f2 += 8; e2 += 8;
        };
#pragma unroll 1
        for (int j = 0; j < NSLOT2; j++) {
          step(&P.tm_h, 192 * (j >> 1) + 64 * (j & 1));
          PTL(222 + j);
          if (j == 3) e2 -= 8;
        }
        s2 = sbase; f2 = bar + B_FULL2; e2 = bar + B_EMPTY2; p2 = 0;
        auto wrap = [&]() { if (f2 == bar + B_FULL2 + NSLOT2 * 8) { s2 = sbase; f2 = bar + B_FULL2; e2 = bar + B_EMPTY2; p2 ^= 1; } };
#pragma unroll 1
        for (int j = NSLOT2; j < 16; j++) { step(&P.tm_h, 192 * (j >> 1) + 64 * (j & 1)); PTL(222 + j); wrap(); }
        TL(6); mbar_wait_trap(bar + B_GO5, 0); fence_async_global(); TL(7);
#pragma unroll 1
        for (int u = 128; u < FF; u += 192) { step(&P.tm_h, u); PTL(238 + u / 192); wrap(); }
        TL(8); mbar_wait_trap(bar + B_GO6, 0); fence_async_global(); TL(9);
#pragma unroll 1
        for (int k = 0; k < 640; k += 64) { step(&P.tm_o, k); PTL(246 + k / 64); wrap(); }
      }
    } else {
      unsigned ep = 0;
      if (lane == 0) ep = ld_epoch() + 1;
      ep = __shfl_sync(0xffffffffu, ep, 0);
      const int par = ep & 1;
      if (warp == 1) {
        if (lane == 0) {
          mbar_wait_trap(bar + B_KVS, 0);
          bulk1d_store(g_wkv + (c * 80 + 5 * r) * 2560, stg + WOUT_KV, 12800);
          bulk_commit();
          bulk_wait0();
          TL(49);
          flag_add_relaxed(FL_PREP + c);
          TL(32);
        }
        __syncwarp();
        flag_wait8(FL_PREP, ep * 16, lane);
        if (lane == 0) {
          mbar_arrive(bar + B_GO2);
          mbar_wait_trap(bar + B_QS, 0);
          for (int t = 0; t < 5; t++) bulk1d_store(g_wqh + (c * 80 + 5 * r + t) * 2304 + 1024, stg + WOUT_Q + t * 1280, 1280);
          bulk_commit();
          bulk_wait0();
          flag_add(FL_W1T + c);
        }
        __syncwarp();
        flag_wait8(FL_W1T, ep * 16, lane);
        if (lane == 0) {
          mbar_arrive(bar + B_GO3);
        }
        __syncwarp();
        flag_wait8(FL_P3W, 3 * ep - 2, lane);
        if (lane == 0) {
          flag_wait(FL_HA + r, ep * 8);
          mbar_arrive(bar + B_GO4);
          sts32(sbase + OFF_T0 + 8, tgate_poll(2, work >> 4, ep));
          mbar_arrive(bar + B_GATE4);
          mbar_wait_trap(bar + B_HBP, 0);
          flag_add(FL_HB + r);
        }
        __syncwarp();
        flag_wait8(FL_P3W, 3 * ep - 1, lane);
        if (lane == 0) {
          flag_wait(FL_HB + r, ep * 8);
          mbar_arrive(bar + B_GO5);
        }
        __syncwarp();
        flag_wait8(FL_P3W, 3 * ep, lane);
        if (lane == 0) mbar_arrive(bar + B_GO6W);
        __syncwarp();
        if (lane == 0) {
          flag_wait(FL_O + r, ep * 32);
          mbar_arrive(bar + B_GO6);
          if (work == 0) g_epoch[0] = ep;
        }
      } else {
        if (warp == 2) {
          if (lane < 27) g_cs[par ^ 1][c * 432 + r * 27 + lane] = 0.f;
          for (int q = lane; q < 60; q += 32) reinterpret_cast<float4*>(&g_kv[par ^ 1][c * 3840 + r * 240])[q] = make_float4(0.f, 0.f, 0.f, 0.f);
          if (lane == 0) {
            mbar_wait_trap(bar + B_SDONE, 0);
            bulk1d_store(&g_stats[r * 128 + c * 16], sbase + OFF_ROWC, 128);
            asm volatile("cp.reduce.async.bulk.global.shared::cta.bulk_group.add.f32 [%0], [%1], %2;" ::"l"(&g_cs[par][c * 432]), "r"(sbase + OFF_CS), "r"(1728) : "memory");
            bulk_commit();
            bulk_wait0();
            flag_add_relaxed(FL_STATS + r);
            flag_add_relaxed(FL_CS + c);
            TL(40);
          }
          __syncwarp();
          flag_wait2(FL_CS + c, ep * 16, FL_STATS + r, ep * 8, lane);
          if (lane == 0) {
            fence_async_global();
            mbar_expect_tx(bar + B_CONST, 1728 + 1024);
            bulk1d(sbase + OFF_CS, &g_cs[par][c * 432], 1728, bar + B_CONST);
            bulk1d(sbase + OFF_ROWC, &g_stats[r * 128], 1024, bar + B_CONST);
            TL(41);
            mbar_wait_trap(bar + B_HAP, 0);
            flag_add(FL_HA + r);
            mbar_wait_trap(bar + B_E2E, 0);
            tgate_arrive(2, work >> 4, ep, T0_DELAY);
            mbar_wait_trap(bar + B_KVP, 0);
            TL(29);
            asm volatile("cp.reduce.async.bulk.global.shared::cta.bulk_group.add.f32 [%0], [%1], %2;" ::"l"(&g_kv[par][c * 3840]), "r"(stg), "r"(15360) : "memory");
            bulk_commit();
            bulk_wait0();
            flag_add_relaxed(FL_KV + c);
            TL(30);
            flag_wait(FL_KV + c, ep * 16);
            fence_async_global();
            mbar_expect_tx(bar + B_KVOK, 15360);
            bulk1d(stg + KVRAW_OFF, &g_kv[par][c * 3840], 15360, bar + B_KVOK);
            TL(43);
          }
        } else {
          mbar_wait_trap(bar + B_PIN, 0);
          const __nv_bfloat16* src = P.w1 + (size_t)(40 * r) * FF + 192 * c + 128 + 2 * lane;
          auto put = [&](const uint32_t (&u)[8], int t) {
            uint8_t* dst = g_wqh + (c * 80 + 5 * r + t) * 2304 + lane * 32;
            *reinterpret_cast<uint4*>(dst) =
                make_uint4(__byte_perm(u[0], u[1], 0x5410), __byte_perm(u[2], u[3], 0x5410), __byte_perm(u[4], u[5], 0x5410), __byte_perm(u[6], u[7], 0x5410));
            *reinterpret_cast<uint4*>(dst + 16) =
                make_uint4(__byte_perm(u[0], u[1], 0x7632), __byte_perm(u[2], u[3], 0x7632), __byte_perm(u[4], u[5], 0x7632), __byte_perm(u[6], u[7], 0x7632));
          };
#pragma unroll 1
          for (int t0 = 0; t0 < 5; t0 += 2) {
            uint32_t tv[2][8];
#pragma unroll
            for (int t = 0; t < 2; t++)
#pragma unroll
              for (int m = 0; m < 8; m++) tv[t][m] = (t0 + t < 5) ? ldg32(src + (8 * (t0 + t) + m) * FF) : 0u;
            put(tv[0], t0);
            if (t0 + 1 < 5) put(tv[1], t0 + 1);
          }
          __syncwarp();
          if (lane == 0) { mbar_arrive(bar + B_QS); TL(39); }
          if (lane == 0) {
            const uint8_t* src = g_wp3 + (c >> 1) * 34 * 20480;
            uint32_t s2 = sbase + 8192, f2 = bar + B_FULL2, e2 = bar + B_EMPTY, p2 = 1;
            mbar_wait_trap(bar + B_GO4, 0); fence_async_global();
#pragma unroll 1
            for (int j = 0; j < 34; j++, src += 20480) {
              if (j == 16) { mbar_wait_trap(bar + B_GO5, 0); fence_async_global(); }
              if (j == 24) { mbar_wait_trap(bar + B_GO6W, 0); fence_async_global(); }
              mbar_wait_trap(e2, p2);
              bulk1d(s2, src, 20480, f2);
              s2 += SLOT2_BYTES; f2 += 8; e2 += 8;
              if (j == 3) e2 -= 8;
              if (f2 == bar + B_FULL2 + NSLOT2 * 8) { s2 = sbase + 8192; f2 = bar + B_FULL2; e2 = bar + B_EMPTY2; p2 = j == 5 ? 0 : p2 ^ 1; }
            }
          }
        }
      }
    }
  } else {
   asm volatile("setmaxnreg.inc.sync.aligned.u32 232;");
   const int w = warp & 3;
   const int t128 = tid & 127;
   const uint32_t rowc0 = sbase + OFF_ROWC + (16 * w + li) * 8;
   const uint32_t csj = sbase + OFF_CS + lj * 8;
   unsigned ep = 0;
   if (lane == 0) ep = ld_epoch() + 1;
   {
     uint32_t a[9];
     const int p0 = 8 * (li >> 1) + 2 * w + (li & 1);
     const int npass = warp < 8 ? 2 : 1;
     uint4 x[10];
     uint32_t w1v[40];
     mbar_wait(bar + B_PIN, 0);
     ep = __shfl_sync(0xffffffffu, ep, 0);
     if (t128 == 0 && warp >= 8) TL(45);
#pragma unroll 1
     for (int pass = 0; pass < npass; pass++) {
       const int m = pass > 0 ? 0 : (warp < 8 ? 2 : 1);
       if (m == 2) {
         const uint32_t id = (li == 2 * lj) ? 0x00003F80u : (li == 2 * lj + 1) ? 0x3F800000u : 0u;
         a[0] = id; a[1] = 0; a[2] = 0; a[3] = id; a[4] = 0; a[5] = 0; a[6] = 0; a[7] = 0; a[8] = li < 4 ? id : 0u;
       } else {
         const uint32_t ph = sbase + OFF_PHI + (w * 400 + 2 * lj * 20 + li) * 2;
         auto phi2 = [&](int o) -> uint32_t { return lds16(ph + o * 2) | (lds16(ph + o * 2 + 40) << 16); };
         a[0] = phi2(0); a[1] = phi2(8); a[2] = phi2(160); a[3] = phi2(168);
         a[4] = lj < 2 ? phi2(320) : 0u;
         a[5] = lj < 2 ? phi2(328) : 0u;
         a[6] = li < 4 ? phi2(16) : 0u;
         a[7] = li < 4 ? phi2(176) : 0u;
         a[8] = (li < 4 && lj < 2) ? phi2(336) : 0u;
       }
       constexpr bool live = true;
       const uint32_t wa = stg + WIN_OFF + m * 6400 + li * 160 + (w * 20 + 2 * lj) * 2;
       float c0[5][4], c1[5][4];
#pragma unroll
       for (int t = 0; t < 5; t++) {
         const uint32_t b0 = lds32(wa + t * 1280), b1 = lds32(wa + t * 1280 + 16), b2 = lj < 2 ? lds32(wa + t * 1280 + 32) : 0u;
         mma16816_z(c0[t], a[0], a[1], a[2], a[3], b0, b1);
         mma16816_z(c1[t], a[6], 0u, a[7], 0u, b0, b1);
         mma16816(c0[t], a[4], a[5], 0u, 0u, b2, 0u);
         mma16816(c1[t], a[8], 0u, 0u, 0u, b2, 0u);
       }
       const uint32_t op = stg + (m == 0 ? WOUT_Q : WOUT_KV + (m == 2 ? 80 * 16 : 0)) + p0 * 16 + 4 * lj;
       const uint32_t cstride = m == 0 ? 1280 : 2560;
       float s0 = 0.f, s1 = 0.f, s2 = 0.f;
#pragma unroll
       for (int t = 0; t < 5; t++) {
         const uint32_t v0 = pack2(c0[t][0], c0[t][1]), v1 = pack2(c0[t][2], c0[t][3]), v2 = pack2(c1[t][0], c1[t][1]);
         if (live) sts32(op + t * cstride, v0);
         if (live) sts32(op + t * cstride + 32 * 16, v1);
         if (live && li < 4) sts32(op + t * cstride + 64 * 16, v2);
         s0 += bf_lo(v0) + bf_hi(v0); s1 += bf_lo(v1) + bf_hi(v1); s2 += bf_lo(v2) + bf_hi(v2);
       }
       s0 += __shfl_xor_sync(0xffffffffu, s0, 1); s1 += __shfl_xor_sync(0xffffffffu, s1, 1); s2 += __shfl_xor_sync(0xffffffffu, s2, 1);
       s0 += __shfl_xor_sync(0xffffffffu, s0, 2); s1 += __shfl_xor_sync(0xffffffffu, s1, 2); s2 += __shfl_xor_sync(0xffffffffu, s2, 2);
       const uint32_t cp = sbase + OFF_CS + ((m == 0 ? 352 : (m == 1 ? 192 : 272)) + p0) * 4;
       if (lj == 0) { sts32(cp, __float_as_uint(s0)); sts32(cp + 128, __float_as_uint(s1)); if (li < 4) sts32(cp + 256, __float_as_uint(s2)); }
       fence_async_smem();
       if (pass == 0) { __syncwarp(); if (lane == 0) mbar_arrive(bar + B_KVS); }
       if (t128 == 0) { if (warp >= 8) TL(46); else if (pass) TL(47); }
       if (pass == 0 && warp >= 8) {
           const __nv_bfloat16* xp = P.x + (size_t)(r * 128 + c * 16 + 4 * w + (lane >> 3)) * DM + (lane & 7) * 8;
#pragma unroll
           for (int k = 0; k < 10; k++) x[k] = ldg128(xp + k * 64);
           if (t128 < 96) {
             const __nv_bfloat16* wp = P.w1 + (size_t)(40 * r) * FF + 192 * c + 2 * t128;
#pragma unroll
             for (int k = 0; k < 40; k++) w1v[k] = ldg32(wp + k * FF);
           }
       } else if (pass) {
         __syncwarp();
         if (lane == 0) { mbar_arrive(bar + B_QS); mbar_arrive(bar + B_SDONE); }
       }
     }
     if (warp >= 8) {
       const int q = 4 * w + (lane >> 3);
      auto sum2 = [](uint32_t v) { return bf_lo(v) + bf_hi(v); };
      float sx = 0.f;
#pragma unroll
      for (int k = 0; k < 10; k++) sx += (sum2(x[k].x) + sum2(x[k].y)) + (sum2(x[k].z) + sum2(x[k].w));
#pragma unroll
      for (int o = 4; o; o >>= 1) sx += __shfl_xor_sync(0xffffffffu, sx, o);
      const float mean = sx * (1.0f / DM);
      auto sq2 = [&](uint32_t v) { const float a = bf_lo(v) - mean, b = bf_hi(v) - mean; return fmaf(a, a, b * b); };
      float ss = 0.f;
#pragma unroll
      for (int k = 0; k < 10; k++) ss += (sq2(x[k].x) + sq2(x[k].y)) + (sq2(x[k].z) + sq2(x[k].w));
#pragma unroll
      for (int o = 4; o; o >>= 1) ss += __shfl_xor_sync(0xffffffffu, ss, o);
      const float var = bf_round(ss * (1.0f / DM));
      const float den = bf_round(sqrt_fast(bf_round(var + 1e-5f)));
      if ((lane & 7) == 0) sts64(sbase + OFF_ROWC + q * 8, __float_as_uint(rcp(den)), __float_as_uint(-bf_round(mean)));
      if (t128 < 96) {
        float t0 = 0.f, t1 = 0.f;
#pragma unroll
        for (int k = 0; k < 40; k++) { t0 += bf_lo(w1v[k]); t1 += bf_hi(w1v[k]); }
        sts64(sbase + OFF_CS + 2 * t128 * 4, __float_as_uint(t0), __float_as_uint(t1));
      }
      fence_async_smem();
      __syncwarp();
      if (lane == 0) mbar_arrive(bar + B_SDONE);
      if (t128 == 0) TL(14);
     }
   }
   if (warp < 8) {
    {
      float acc[2][64];
      mainloop<10>(0, lane, NB_A2B, [&](uint32_t s, int kb) {
        static_for<0, 4>([&](auto KS) {
          constexpr int ks = KS.value;
          const uint64_t db = desc_sw128<16384 + ks * 2048, 8192>(s);
          wg_n128_tb(acc[0], desc_sw128<ks * 32>(s), db, ks ? 1 : kb);
          wg_n128_tb(acc[1], desc_sw128<8192 + ks * 32>(s), db, ks ? 1 : kb);
        });
      }, [&](int kb) {
      });
      reg_fence(acc[0]); reg_fence(acc[1]);
      if (t128 == 0) TL(16);
      mbar_wait(bar + B_CONST, 0);
      if (t128 == 0) TL(17);
      float2 cs[16];
#pragma unroll
      for (int g = 0; g < 16; g++) cs[g] = lds_f2(csj + 32 * g);
      __nv_bfloat16* hp = g_h + (size_t)(r * 128 + 16 * w + li) * FF + 192 * c + 8 * lj;
#pragma unroll 1
      for (int mb = 0; mb < 2; mb++) {
        epi_h<16, 0>(acc[0], cs, lds_f2(rowc0 + mb * 512), lds_f2(rowc0 + mb * 512 + 64), hp + mb * 64 * FF);
#pragma unroll
        for (int i = 0; i < 64; i++) acc[0][i] = acc[1][i];
        if (t128 == 0) TL(56 + mb);
      }
      __syncwarp();
      if (lane == 0) mbar_arrive(bar + B_HAP);
      if (t128 == 0) TL(18);
    }
    {
      float acc[2][72];
      nb_sync(NB_B2A, 256);
      if (t128 == 0) TL(19);
      mainloop<10>(20, lane, NB_A2B, [&](uint32_t s, int kb) {
        static_for<0, 4>([&](auto KS) {
          constexpr int ks = KS.value;
          const uint64_t db = desc_nosw<16384 + ks * 4608, 2304, 128>(s);
          wg_n144(acc[0], desc_sw128<ks * 32>(s), db, ks ? 1 : kb);
          wg_n144(acc[1], desc_sw128<8192 + ks * 32>(s), db, ks ? 1 : kb);
        });
      });
      reg_fence(acc[0]); reg_fence(acc[1]);
      if (t128 == 0) TL(20);
      {
        float2 cs[8];
#pragma unroll
        for (int g = 0; g < 8; g++) cs[g] = lds_f2(csj + 128 * 4 + 32 * g);
        __nv_bfloat16* hp = g_h + (size_t)(r * 128 + 16 * w + li) * FF + 192 * c + 128 + 8 * lj;
#pragma unroll 1
        for (int mb = 0; mb < 2; mb++) {
          epi_h<8, 0>(acc[0], cs, lds_f2(rowc0 + mb * 512), lds_f2(rowc0 + mb * 512 + 64), hp + mb * 64 * FF);
#pragma unroll
          for (int i = 0; i < 32; i++) acc[0][i] = acc[1][i];
        }
      }
      __syncwarp();
      if (lane == 0) mbar_arrive(bar + B_HBP);
      if (t128 == 0) TL(21);
      float bk[4][20];
      {
        float2 cq[10];
#pragma unroll
        for (int g = 0; g < 10; g++) cq[g] = lds_f2(csj + 352 * 4 + 32 * g);
#pragma unroll
        for (int t = 0; t < 4; t++) {
          const float nm = lds_f2(rowc0 + (t >> 1) * 512 + (t & 1) * 64).y;
#pragma unroll
          for (int g = 0; g < 10; g++) {
            bk[t][2 * g] = fmaf(nm, cq[g].x, acc[t >> 1][32 + 4 * g + 2 * (t & 1)]);
            bk[t][2 * g + 1] = fmaf(nm, cq[g].y, acc[t >> 1][32 + 4 * g + 2 * (t & 1) + 1]);
          }
        }
      }
#pragma unroll 1
      for (int mb = 0; mb < 2; mb++) {
        float e0[40], e1[40];
        softmax_exp(bk[0], lds_f2(rowc0 + mb * 512).x * LOG2E, e0);
        softmax_exp(bk[1], lds_f2(rowc0 + mb * 512 + 64).x * LOG2E, e1);
#pragma unroll
        for (int i = 0; i < 20; i++) { bk[0][i] = bk[2][i]; bk[1][i] = bk[3][i]; }
        if (split_block()) {
          uint32_t f0[20], f1[20];
          softmax_norm(e0, f0);
          softmax_norm(e1, f1);
#pragma unroll
          for (int i = 0; i < 20; i++) { bk[2][i] = __uint_as_float(f0[i]); bk[3][i] = __uint_as_float(f1[i]); }
        }
      }
      if (t128 == 0) TL(52);
      {
        mbar_wait(bar + B_KVOK, 0);
            if (t128 == 0) TL(22);
            int tl_;
            asm volatile("mov.u32 %0, %1;" : "=r"(tl_) : "r"(t128));
            float4 v0[4], v1[4];
#pragma unroll
            for (int u = 0; u < 4; u++) {
              const int item = tl_ + 128 * u, t = item >> 2, kc = t / 6, q = t - kc * 6;
              if (item < 480) {
                const uint32_t sp = stg + KVRAW_OFF + (((item & 3) * 40 + 2 * kc) * 24 + 4 * q) * 4;
                const uint4 a_ = lds128(sp), b_ = lds128(sp + 96);
                v0[u] = make_float4(__uint_as_float(a_.x), __uint_as_float(a_.y), __uint_as_float(a_.z), __uint_as_float(a_.w));
                v1[u] = make_float4(__uint_as_float(b_.x), __uint_as_float(b_.y), __uint_as_float(b_.z), __uint_as_float(b_.w));
              }
            }
            nb_sync(NB_A, 128);
            const int hj = tl_ & 3;
            const bool odd = (tl_ >> 2) & 1;
            const uint32_t m0 = hj == 0 ? ~0u : 0u, m1 = hj == 1 ? ~0u : 0u, m2 = hj == 2 ? ~0u : 0u, m3 = hj == 3 ? ~0u : 0u;
            const uint32_t o0 = odd ? 16u : 0u, o1 = 16u - o0;
#pragma unroll
            for (int u = 0; u < 4; u++) {
              const int item = tl_ + 128 * u, t = item >> 2, kc = t / 6, q = t - kc * 6;
              if (item < 480) {
                const uint32_t dst = stg + kc * BKV_LBO + hj * 32 + 2 * q * 128;
                uint32_t w0 = pack2(v0[u].x, v1[u].x), w1 = pack2(v0[u].y, v1[u].y);
                const uint32_t w2 = pack2(v0[u].z, v1[u].z), w3 = pack2(v0[u].w, v1[u].w);
                if (q == 5) w1 = 0u;
                const uint32_t a0 = odd ? w1 : w0, a1 = odd ? w0 : w1, b0 = odd ? w3 : w2, b1 = odd ? w2 : w3;
                sts128(dst + o0, a0 & m0, a0 & m1, a0 & m2, a0 & m3);
                sts128(dst + o1, a1 & m0, a1 & m1, a1 & m2, a1 & m3);
                if (q < 5) {
                  sts128(dst + 128 + o0, b0 & m0, b0 & m1, b0 & m2, b0 & m3);
                  sts128(dst + 128 + o1, b1 & m0, b1 & m1, b1 & m2, b1 & m3);
                }
              }
            }
            fence_async_smem();
            nb_sync(NB_A, 128);
            if (t128 == 0) TL(44);
      }
      {
        float ao[2][44];
        wg_fence();
        static_for<0, 20>([&](auto I) {
          constexpr int mb = I.value / 10, ks = I.value % 10;
          wg_n88_rs(ao[mb], __float_as_uint(bk[2 * mb][2 * ks]), __float_as_uint(bk[2 * mb + 1][2 * ks]), __float_as_uint(bk[2 * mb][2 * ks + 1]),
                    __float_as_uint(bk[2 * mb + 1][2 * ks + 1]), desc_nosw<2 * ks * BKV_LBO, BKV_LBO, 128>(stg >> 4), ks != 0);
        });
        wg_commit();
        wg_wait<0>();
        reg_fence(ao[0]); reg_fence(ao[1]);
        if (t128 == 0) TL(53);
        nb_sync(NB_A, 128);
        const uint32_t ost = stg + w * 5120;
#pragma unroll
        for (int mb = 0; mb < 2; mb++) {
          const float i0 = rcp(ao[mb][40] + 1e-6f), i1 = rcp(ao[mb][42] + 1e-6f);
          const uint32_t oa = ost + mb * 2560 + li * 160 + lj * 40;
#pragma unroll
          for (int m = 0; m < 5; m++) {
            sts64(oa + m * 8, pack2(ao[mb][8 * m] * i0, ao[mb][8 * m + 1] * i0), pack2(ao[mb][8 * m + 4] * i0, ao[mb][8 * m + 5] * i0));
            sts64(oa + 8 * 160 + m * 8, pack2(ao[mb][8 * m + 2] * i1, ao[mb][8 * m + 3] * i1), pack2(ao[mb][8 * m + 6] * i1, ao[mb][8 * m + 7] * i1));
          }
        }
        fence_async_smem();
        __syncwarp();
        if (lane == 0) {
          tma2d_store(&P.tm_ost, 80 * c, r * 128 + 16 * w, ost);
          tma2d_store(&P.tm_ost, 80 * c, r * 128 + 64 + 16 * w, ost + 2560);
          bulk_commit();
        }
      }
      if (t128 == 0) TL(54);
      if (lane == 0) { bulk_wait0(); if (t128 == 0) TL(55); flag_add_relaxed(FL_O + r); }
      nb_sync(NB_A, 128);
      if (t128 == 0) {
        TL(23);
        mbar_expect_tx(bar + B_XF, 20480);
        tma2d(stg + XO_OFF, &P.tm_xt, 160 * (c >> 1), r * 128 + 64 * (c & 1), bar + B_XF);
      }
      nb_arrive(NB_STG, 256);
    }
    {
      float acc[80];
      nb_sync(NB_B2A, 256);
      if (t128 == 0) TL(24);
      mainloop<10, true>(24, lane, -1, [&](uint32_t s, int kb) {
        static_for<0, 4>([&](auto KS) {
          constexpr int ks = KS.value;
          wg_n160(acc, desc_sw128<ks * 32>(s), desc_nosw<8192 + ks * 5120, 2560, 128>(s), ks ? 1 : kb);
        });
      });
      reg_fence(acc);
      if (t128 == 0) TL(25);
      mbar_wait(bar + B_XF, 0);
      nb_sync(NB_G, 256);
      const uint32_t xo = stg + XO_OFF + 16 * w * 320;
#pragma unroll
      for (int rs = 0; rs < 2; rs++) {
        const uint32_t xa = xo + (li + 8 * rs) * 320 + lj * 80;
#pragma unroll
        for (int q = 0; q < 5; q++) {
          const uint4 gv = lds128(stg + (rs * 5 + q) * 2048 + t128 * 16), xv = lds128(xa + q * 16);
          const uint32_t gq[4] = {gv.x, gv.y, gv.z, gv.w}, xq[4] = {xv.x, xv.y, xv.z, xv.w};
          uint32_t o[4];
#pragma unroll
          for (int t = 0; t < 4; t++) {
            const int g = 4 * q + t;
            asm("fma.rn.bf16x2 %0, %1, %2, %3;" : "=r"(o[t]) : "r"(pack2(acc[4 * g + 2 * rs], acc[4 * g + 2 * rs + 1])), "r"(gq[t]), "r"(xq[t]));
          }
          sts128(xa + q * 16, o[0], o[1], o[2], o[3]);
        }
      }
      fence_async_smem();
      __syncwarp();
      if (lane == 0) { tma2d_store(&P.tm_out, 160 * (c >> 1), r * 128 + 64 * (c & 1) + 16 * w, xo); bulk_commit(); }
      if (lane == 0) bulk_wait_read0();
      if (t128 == 0) { TL(26); TLG(27); }
    }
   } else {
    {
      float acc[2][80];
      nb_sync(NB_A2B, 256);
      if (t128 == 0) TL(33);
      mainloop<10>(10, lane, T3_GO < 0 ? NB_B2A : -1, [&](uint32_t s, int kb) {
        static_for<0, 4>([&](auto KS) {
          constexpr int ks = KS.value;
          const uint64_t db = desc_nosw<16384 + ks * 5120, 2560, 128>(s);
          wg_n160(acc[0], desc_sw128<ks * 32>(s), db, ks ? 1 : kb);
          wg_n160(acc[1], desc_sw128<8192 + ks * 32>(s), db, ks ? 1 : kb);
        });
      });
      reg_fence(acc[0]); reg_fence(acc[1]);
      if (t128 == 0) TL(34);
      mbar_wait(bar + B_CONST, 0);
      mbar_wait(bar + B_GO3, 0);
      uint32_t vp[4][10];
      {
        float2 cv[10];
#pragma unroll
        for (int g = 0; g < 10; g++) cv[g] = lds_f2(csj + 272 * 4 + 32 * g);
#pragma unroll
        for (int t = 0; t < 4; t++) {
          const float2 rc = lds_f2(rowc0 + (t >> 1) * 512 + (t & 1) * 64);
#pragma unroll
          for (int g = 0; g < 10; g++)
            vp[t][g] = pack2(rc.x * fmaf(rc.y, cv[g].x, acc[t >> 1][40 + 4 * g + 2 * (t & 1)]), rc.x * fmaf(rc.y, cv[g].y, acc[t >> 1][40 + 4 * g + 2 * (t & 1) + 1]));
        }
      }
      float bk[4][20];
      {
        float2 ck[10];
#pragma unroll
        for (int g = 0; g < 10; g++) ck[g] = lds_f2(csj + 192 * 4 + 32 * g);
#pragma unroll
        for (int t = 0; t < 4; t++) {
          const float nm = lds_f2(rowc0 + (t >> 1) * 512 + (t & 1) * 64).y;
#pragma unroll
          for (int g = 0; g < 10; g++) {
            bk[t][2 * g] = fmaf(nm, ck[g].x, acc[t >> 1][4 * g + 2 * (t & 1)]);
            bk[t][2 * g + 1] = fmaf(nm, ck[g].y, acc[t >> 1][4 * g + 2 * (t & 1) + 1]);
          }
        }
      }
      if (t128 == 0) TL(28);
      float kvd[4][12];
#pragma unroll 1
      for (int mb = 0; mb < 2; mb++) {
        float e0[40], e1[40];
        softmax_exp(bk[0], lds_f2(rowc0 + mb * 512).x * LOG2E, e0);
        softmax_exp(bk[1], lds_f2(rowc0 + mb * 512 + 64).x * LOG2E, e1);
#pragma unroll
        for (int i = 0; i < 20; i++) { bk[0][i] = bk[2][i]; bk[1][i] = bk[3][i]; }
        if (t128 == 0) TL(58 + 2 * mb);
        if (mb == T3_GO) nb_arrive(NB_B2A, 256);
        if (mb == 1 && lane == 0) mbar_arrive(bar + B_E2E);
        wg_wait<0>();
        nb_sync(NB_B, 128);
        if (split_block()) {
          uint32_t f[2][20];
          softmax_norm(e0, f[0]);
          softmax_norm(e1, f[1]);
#pragma unroll
          for (int rs = 0; rs < 2; rs++) {
            const int kg = 2 * w + rs;
            const uint32_t pa = stg + lj * PHI_HS + kg * 128 + li * 16;
#pragma unroll
            for (int b = 0; b < 5; b++) sts128(pa + b * 1024, f[rs][4 * b], f[rs][4 * b + 1], f[rs][4 * b + 2], f[rs][4 * b + 3]);
            const uint32_t va = stg + V_OFF + lj * V_HS + kg * 128 + li * 16;
            sts128(va, vp[rs][0], vp[rs][1], vp[rs][2], vp[rs][3]);
            sts128(va + 1024, vp[rs][4], vp[rs][5], vp[rs][6], vp[rs][7]);
            sts128(va + 2048, vp[rs][8], vp[rs][9], 0x00003F80u, 0u);
          }
        }
#pragma unroll
        for (int i = 0; i < 10; i++) { vp[0][i] = vp[2][i]; vp[1][i] = vp[3][i]; }
        if (t128 == 0) TL(59 + 2 * mb);
        fence_async_smem();
        nb_sync(NB_B, 128);
        wg_fence();
        static_for<0, 16>([&](auto I) {
          constexpr int hh_ = I.value & 3, ks = I.value >> 2;
          wg_n24_tatb(kvd[hh_], desc_nosw<hh_ * PHI_HS + ks * 256, 128, 1024>(stg >> 4), desc_nosw<V_OFF + hh_ * V_HS + ks * 256, 128, 1024>(stg >> 4), ks ? 1 : mb);
        });
        wg_commit();
        if (t128 == 0) TL(62 + mb);
      }
      wg_wait<0>();
#pragma unroll
      for (int hh_ = 0; hh_ < 4; hh_++) reg_fence(kvd[hh_]);
      nb_sync(NB_B, 128);
#pragma unroll
      for (int rs = 0; rs < 2; rs++) {
        const int fr = 16 * w + li + 8 * rs;
        if (fr < 40) {
#pragma unroll
          for (int hh_ = 0; hh_ < 4; hh_++)
#pragma unroll
            for (int g = 0; g < 3; g++)
              sts64(stg + ((hh_ * 40 + fr) * 24 + 8 * g + 2 * lj) * 4, __float_as_uint(kvd[hh_][4 * g + 2 * rs]), __float_as_uint(kvd[hh_][4 * g + 2 * rs + 1]));
        }
      }
      fence_async_smem();
      __syncwarp();
      if (lane == 0) mbar_arrive(bar + B_KVP);
      if (t128 == 0) TL(35);
    }
    {
      float acc[80];
      mbar_wait(bar + B_GATE4, 0);
      nb_sync(NB_A2B, 256);
      wait_until(lds32(sbase + OFF_T0 + 8));
      if (t128 == 0) TL(36);
      mainloop<24, true>(0, lane, NB_B2A, [&](uint32_t s, int kb) {
        static_for<0, 4>([&](auto KS) {
          constexpr int ks = KS.value;
          wg_n160(acc, desc_sw128<ks * 32>(s), desc_nosw<8192 + ks * 5120, 2560, 128>(s), ks ? 1 : kb);
        });
      });
      reg_fence(acc);
      if (t128 == 0) TL(37);
      uint32_t gw[40];
#pragma unroll
      for (int rs = 0; rs < 2; rs++)
#pragma unroll
        for (int g = 0; g < 20; g++) gw[rs * 20 + g] = pack2(silu_half(0.5f * acc[4 * g + 2 * rs]), silu_half(0.5f * acc[4 * g + 2 * rs + 1]));
      nb_sync(NB_STG, 256);
#pragma unroll
      for (int q = 0; q < 10; q++) sts128(stg + q * 2048 + t128 * 16, gw[4 * q], gw[4 * q + 1], gw[4 * q + 2], gw[4 * q + 3]);
      nb_arrive(NB_G, 256);
      if (t128 == 0) TL(38);
    }
   }
  }
}

typedef CUresult (*EncodeFn)(CUtensorMap*, CUtensorMapDataType, cuuint32_t, void*, const cuuint64_t*, const cuuint64_t*, const cuuint32_t*, const cuuint32_t*,
                             CUtensorMapInterleave, CUtensorMapSwizzle, CUtensorMapL2promotion, CUtensorMapFloatOOBfill);

static void encode2d(EncodeFn enc, CUtensorMap* tm, const void* base, uint64_t cols, uint64_t rows, uint32_t bc, uint32_t br, bool swz) {
  cuuint64_t gd[2] = {cols, rows};
  cuuint64_t gs[1] = {cols * 2};
  cuuint32_t bx[2] = {bc, br};
  cuuint32_t es[2] = {1, 1};
  enc(tm, CU_TENSOR_MAP_DATA_TYPE_BFLOAT16, 2, const_cast<void*>(base), gd, gs, bx, es, CU_TENSOR_MAP_INTERLEAVE_NONE,
      swz ? CU_TENSOR_MAP_SWIZZLE_128B : CU_TENSOR_MAP_SWIZZLE_NONE, CU_TENSOR_MAP_L2_PROMOTION_L2_128B, CU_TENSOR_MAP_FLOAT_OOB_FILL_NONE);
}

}

extern "C" void kernel_launch(void* const* d_in, const int* in_sizes, int n_in, void* d_out, int out_size) {
  using namespace hh;
  (void)in_sizes; (void)n_in; (void)out_size;
  static EncodeFn enc = nullptr;
  static void *p_h = nullptr, *p_o = nullptr;
  if (!enc) {
    void* fn = nullptr;
    cudaDriverEntryPointQueryResult qr;
    cudaGetDriverEntryPoint("cuTensorMapEncodeTiled", &fn, cudaEnableDefault, &qr);
    enc = (EncodeFn)fn;
    cudaGetSymbolAddress(&p_h, g_h);
    cudaGetSymbolAddress(&p_o, g_o);
    cudaFuncSetAttribute(fused_kernel, cudaFuncAttributeMaxDynamicSharedMemorySize, SMEM_ALLOC);
  }
  Params P;
  P.x = (const __nv_bfloat16*)d_in[0];
  P.wqkv = (const __nv_bfloat16*)d_in[1];
  P.wphi = (const __nv_bfloat16*)d_in[2];
  P.wo = (const __nv_bfloat16*)d_in[3];
  P.w1 = (const __nv_bfloat16*)d_in[5];
  P.w2 = (const __nv_bfloat16*)d_in[6];
  P.out = (__nv_bfloat16*)d_out;
  encode2d(enc, &P.tm_x, P.x, DM, SEQ, 64, 128, true);
  encode2d(enc, &P.tm_h, p_h, FF, SEQ, 64, 64, true);
  encode2d(enc, &P.tm_o, p_o, DM, SEQ, 64, 64, true);
  encode2d(enc, &P.tm_xt, P.x, DM, SEQ, 160, 64, false);
  encode2d(enc, &P.tm_ost, p_o, DM, SEQ, 80, 16, false);
  encode2d(enc, &P.tm_out, d_out, DM, SEQ, 160, 16, false);
  encode2d(enc, &P.tm_wqkv, P.wqkv, 1920, DM, 80, 40, false);
  encode2d(enc, &P.tm_w2, P.w2, DM, FF, 160, 64, false);
  encode2d(enc, &P.tm_wo, P.wo, DM, DM, 160, 64, false);
  {
    cuuint64_t gd[3] = {64, DM, FF / 64};
    cuuint64_t gs[2] = {FF * 2, 128};
    cuuint32_t bx[3] = {64, 64, 2};
    cuuint32_t es[3] = {1, 1, 1};
    enc(&P.tm_w1b, CU_TENSOR_MAP_DATA_TYPE_BFLOAT16, 3, const_cast<__nv_bfloat16*>(P.w1), gd, gs, bx, es, CU_TENSOR_MAP_INTERLEAVE_NONE,
        CU_TENSOR_MAP_SWIZZLE_128B, CU_TENSOR_MAP_L2_PROMOTION_L2_128B, CU_TENSOR_MAP_FLOAT_OOB_FILL_NONE);
  }
  fused_kernel<<<NGRID, 384, SMEM_ALLOC, cudaStreamPerThread>>>(P);
}
```
